```python
import torch

def _softmax(x, axis=-1):
    return torch.softmax(x, dim=axis)
def _gelu(x):
    return torch.nn.functional.gelu(x, approximate="tanh")
def _silu(x):
    return torch.nn.functional.silu(x)
def _sigmoid(x):
    return torch.sigmoid(x)
def _layernorm(x, axis=-1, eps=1e-5):
    m = x.mean(dim=axis, keepdim=True)
    v = x.var(dim=axis, keepdim=True, unbiased=False)
    return (x - m) / torch.sqrt(v + eps)
def _scatter_add(tgt, idx, src, axis=0):
    return tgt.clone().index_add_(axis, idx, src)
def _segment_sum(src, seg, n):
    out = torch.zeros((n,) + src.shape[1:], dtype=src.dtype)
    return out.index_add_(0, seg, src)
def _pad(x, pw):
    flat = tuple(v for pair in reversed(pw) for v in pair)
    return torch.nn.functional.pad(x, flat)

kernel_name = 'standalone__kv_cache_quant_int4_int2_kv_with_per_channel_or_per_token_scales__prompt'

def setup_inputs():

    _w = (lambda a: (lambda t: t.to(torch.bfloat16) if t.is_floating_point() else t)(torch.as_tensor(a)))
    B = 1
    Sq = 2048
    Skv = 2048
    Hq = 32
    Hkv = 32
    Dh = 192
    bits = 8
    G = 64
    if G <= 0 or G >= Skv:
        G = max(1, Skv // 2)
    Skv = (Skv // G) * G
    ngk = Skv // G
    qmax = (1 << bits) - 1
    return {
        "q": _w((lambda *s: torch.randn(*s, dtype=torch.bfloat16) * 0.2)(B, Hq, Sq, Dh)),
        "qk": _w(torch.randint(0, qmax + 1, (B, Hkv, Skv, Dh)).to(torch.int32)),
        "qv": _w(torch.randint(0, qmax + 1, (B, Hkv, Skv, Dh)).to(torch.int32)),
        "k_scales": _w(torch.abs((lambda *s: torch.randn(*s, dtype=torch.bfloat16) * 0.2)(B, Hkv, ngk, Dh)) * 0.05 + 0.02),
        "k_zeros": _w((lambda *s: torch.randn(*s, dtype=torch.bfloat16) * 0.2)(B, Hkv, ngk, Dh) + float(qmax) / 2.0),
        "v_scales": _w(torch.abs((lambda *s: torch.randn(*s, dtype=torch.bfloat16) * 0.05)(B, Hkv, Skv, 1)) * 0.05 + 0.02),
        "v_zeros": _w((lambda *s: torch.randn(*s, dtype=torch.bfloat16) * 0.05)(B, Hkv, Skv, 1) + float(qmax) / 2.0),
    }

def reference(q, qk, qv, k_scales, k_zeros, v_scales, v_zeros):
    B, Hq, Sq, Dh = q.shape
    Hkv, Skv = qk.shape[1], qk.shape[2]
    ngk = k_scales.shape[2]
    G = Skv // ngk
    ks = (lambda x, n, axis: torch.repeat_interleave(x, n, dim=axis))(k_scales, G, axis=2)
    kz = (lambda x, n, axis: torch.repeat_interleave(x, n, dim=axis))(k_zeros, G, axis=2)
    k = ((lambda x, dt: x.to(dt))(qk, q.dtype) - kz) * ks
    v = ((lambda x, dt: x.to(dt))(qv, q.dtype) - v_zeros) * v_scales
    rep = Hq // Hkv
    if rep > 1:
        k = (lambda x, n, axis: torch.repeat_interleave(x, n, dim=axis))(k, rep, axis=1)
        v = (lambda x, n, axis: torch.repeat_interleave(x, n, dim=axis))(v, rep, axis=1)
    scale = float(Dh) ** -0.5
    logits = torch.einsum("bhqd,bhkd->bhqk", q, k) * scale
    p = _softmax(logits, axis=-1)
    o = torch.einsum("bhqk,bhkd->bhqd", p, v)
    return o
```

```cpp
#include <cuda_runtime.h>
#include <cuda_bf16.h>
#include <cuda.h>
#include <stdint.h>

namespace {

constexpr int kH = 32, kS = 2048, kD = 192;
constexpr int kGroupTok = 64;
constexpr int kBN = 128;
constexpr int kNBlk = kS / kBN;
constexpr int kWaves = 4;
constexpr int kSteps = kWaves * kNBlk;
constexpr int kTileBytes = kBN * kD * 2;
constexpr int kOwners = 128, kHelpers = 4;
constexpr int kTail = 2;
constexpr int kOwn = kSteps - kTail;
constexpr uint32_t kHelperDelay = 52000, kHelperPrepare = 12000;
static_assert(kTail == 2, "two blocks");
constexpr int kProbSums = 4 * 16384, kProbExtra = kProbSums + 512, kProbBytes = kProbExtra + 2048;
constexpr int kFlagTarget = 48;
constexpr int kFlagsPerGroup = kSteps;
constexpr float kLazyAbove = 15.f, kLazyBelow = 7.f;
constexpr int kLead = 3;
constexpr int kRing = 2 * kLead + 2;
static_assert((kRing & (kRing - 1)) == 0, "power of two");
constexpr int kBarPolls = 1 << 13, kFlagPolls = 1 << 16;

constexpr uint32_t kGroupStagger = 250, kQDelay = 2300, kQStagger = 520;
constexpr int kStatStep = 9;
static_assert(kStatStep + kLead < 15, "the first block of a head is expanded after its statistics have arrived");
constexpr uint32_t kOffsetFactor = 0x3E553E55u;
constexpr int kExpSplit = 32;
constexpr int kChunkBytes = kBN * 128;
constexpr int kSmemQ = 0;
constexpr int kSmemK = kTileBytes;
constexpr int kSmemV = kSmemK + 5 * kChunkBytes;
constexpr int kSmemBar = kSmemV + 2 * kTileBytes;
constexpr int kOffK = 256, kParV = kOffK + 2 * kD * 2, kBarBytes = kParV + 128;
constexpr int kSmemTotal = kSmemBar + kBarBytes + 1024;

__host__ __device__ constexpr int slot_p(int j, int w) { return (3 * kOwn + 2 * j + w) % 5; }

constexpr int kBarFullK01 = 0, kBarFullV = 16, kBarEmptyK12 = 32, kBarEmptyV = 48, kBarFullQ = 64, kBarEmptyQ = 80,
              kBarFullK2 = 96, kBarEmptyK0 = 104, kBarStage = 112, kBarStaged = 128, kBarFullV2 = 144,
              kBarFullQ2 = 152, kBarCodes = 168, kBarTail = 176, kProgress = 224, kDummy = 228, kBarParams = 232,
              kBarUnits = 240;

__device__ __align__(1024) uint4 g_scratch[(size_t)8 * kRing * 2 * kTileBytes / 16];
constexpr int kFlagHelper = 8 * kFlagsPerGroup, kFlagStats = kFlagHelper + 8, kFlagDone = kFlagStats + 8;
__device__ __align__(16) unsigned g_flags[kFlagDone + 1];
constexpr int kHelperImages = kOwners * kProbBytes, kHeadStats = kHelperImages + 8 * kTail * kTileBytes;
__device__ __align__(1024) uint4 g_prob[(kHeadStats + kH * 512) / 16];

__device__ __forceinline__ void wgmma_ss_n128(float (&d)[64], uint64_t da, uint64_t db, int scale_d) {
  asm volatile("{\n.reg .pred p;\nsetp.ne.b32 p, %66, 0;\n"
    "wgmma.mma_async.sync.aligned.m64n128k16.f32.bf16.bf16 "
    "{%0, %1, %2, %3, %4, %5, %6, %7, %8, %9, %10, %11, %12, %13, %14, %15, %16, %17, %18, %19, %20, %21, %22, %23, %24, %25, %26, %27, %28, %29, %30, %31, %32, %33, %34, %35, %36, %37, %38, %39, %40, %41, %42, %43, %44, %45, %46, %47, %48, %49, %50, %51, %52, %53, %54, %55, %56, %57, %58, %59, %60, %61, %62, %63}, %64, %65, p, 1, 1, 0, 0;\n}\n"
    : "+f"(d[0]), "+f"(d[1]), "+f"(d[2]), "+f"(d[3]), "+f"(d[4]), "+f"(d[5]), "+f"(d[6]), "+f"(d[7]), "+f"(d[8]), "+f"(d[9]), "+f"(d[10]), "+f"(d[11]), "+f"(d[12]), "+f"(d[13]), "+f"(d[14]), "+f"(d[15]), "+f"(d[16]), "+f"(d[17]), "+f"(d[18]), "+f"(d[19]), "+f"(d[20]), "+f"(d[21]), "+f"(d[22]), "+f"(d[23]), "+f"(d[24]), "+f"(d[25]), "+f"(d[26]), "+f"(d[27]), "+f"(d[28]), "+f"(d[29]), "+f"(d[30]), "+f"(d[31]), "+f"(d[32]), "+f"(d[33]), "+f"(d[34]), "+f"(d[35]), "+f"(d[36]), "+f"(d[37]), "+f"(d[38]), "+f"(d[39]), "+f"(d[40]), "+f"(d[41]), "+f"(d[42]), "+f"(d[43]), "+f"(d[44]), "+f"(d[45]), "+f"(d[46]), "+f"(d[47]), "+f"(d[48]), "+f"(d[49]), "+f"(d[50]), "+f"(d[51]), "+f"(d[52]), "+f"(d[53]), "+f"(d[54]), "+f"(d[55]), "+f"(d[56]), "+f"(d[57]), "+f"(d[58]), "+f"(d[59]), "+f"(d[60]), "+f"(d[61]), "+f"(d[62]), "+f"(d[63])
    : "l"(da), "l"(db), "r"(scale_d));
}
__device__ __forceinline__ void wgmma_rs_n64t(float (&d)[32], uint32_t a0, uint32_t a1, uint32_t a2, uint32_t a3, uint64_t db, int scale_d) {
  asm volatile("{\n.reg .pred p;\nsetp.ne.b32 p, %37, 0;\n"
    "wgmma.mma_async.sync.aligned.m64n64k16.f32.f16.f16 "
    "{%0, %1, %2, %3, %4, %5, %6, %7, %8, %9, %10, %11, %12, %13, %14, %15, %16, %17, %18, %19, %20, %21, %22, %23, %24, %25, %26, %27, %28, %29, %30, %31}, {%32, %33, %34, %35}, %36, p, 1, 1, 1;\n}\n"
    : "+f"(d[0]), "+f"(d[1]), "+f"(d[2]), "+f"(d[3]), "+f"(d[4]), "+f"(d[5]), "+f"(d[6]), "+f"(d[7]), "+f"(d[8]), "+f"(d[9]), "+f"(d[10]), "+f"(d[11]), "+f"(d[12]), "+f"(d[13]), "+f"(d[14]), "+f"(d[15]), "+f"(d[16]), "+f"(d[17]), "+f"(d[18]), "+f"(d[19]), "+f"(d[20]), "+f"(d[21]), "+f"(d[22]), "+f"(d[23]), "+f"(d[24]), "+f"(d[25]), "+f"(d[26]), "+f"(d[27]), "+f"(d[28]), "+f"(d[29]), "+f"(d[30]), "+f"(d[31])
    : "r"(a0), "r"(a1), "r"(a2), "r"(a3), "l"(db), "r"(scale_d));
}
__device__ __forceinline__ void wgmma_rs_n192t(float (&d)[96], uint32_t a0, uint32_t a1, uint32_t a2, uint32_t a3, uint64_t db, int scale_d) {
  asm volatile("{\n.reg .pred p;\nsetp.ne.b32 p, %101, 0;\n"
    "wgmma.mma_async.sync.aligned.m64n192k16.f32.f16.f16 "
    "{%0, %1, %2, %3, %4, %5, %6, %7, %8, %9, %10, %11, %12, %13, %14, %15, %16, %17, %18, %19, %20, %21, %22, %23, %24, %25, %26, %27, %28, %29, %30, %31, %32, %33, %34, %35, %36, %37, %38, %39, %40, %41, %42, %43, %44, %45, %46, %47, %48, %49, %50, %51, %52, %53, %54, %55, %56, %57, %58, %59, %60, %61, %62, %63, %64, %65, %66, %67, %68, %69, %70, %71, %72, %73, %74, %75, %76, %77, %78, %79, %80, %81, %82, %83, %84, %85, %86, %87, %88, %89, %90, %91, %92, %93, %94, %95}, {%96, %97, %98, %99}, %100, p, 1, 1, 1;\n}\n"
    : "+f"(d[0]), "+f"(d[1]), "+f"(d[2]), "+f"(d[3]), "+f"(d[4]), "+f"(d[5]), "+f"(d[6]), "+f"(d[7]), "+f"(d[8]), "+f"(d[9]), "+f"(d[10]), "+f"(d[11]), "+f"(d[12]), "+f"(d[13]), "+f"(d[14]), "+f"(d[15]), "+f"(d[16]), "+f"(d[17]), "+f"(d[18]), "+f"(d[19]), "+f"(d[20]), "+f"(d[21]), "+f"(d[22]), "+f"(d[23]), "+f"(d[24]), "+f"(d[25]), "+f"(d[26]), "+f"(d[27]), "+f"(d[28]), "+f"(d[29]), "+f"(d[30]), "+f"(d[31]), "+f"(d[32]), "+f"(d[33]), "+f"(d[34]), "+f"(d[35]), "+f"(d[36]), "+f"(d[37]), "+f"(d[38]), "+f"(d[39]), "+f"(d[40]), "+f"(d[41]), "+f"(d[42]), "+f"(d[43]), "+f"(d[44]), "+f"(d[45]), "+f"(d[46]), "+f"(d[47]), "+f"(d[48]), "+f"(d[49]), "+f"(d[50]), "+f"(d[51]), "+f"(d[52]), "+f"(d[53]), "+f"(d[54]), "+f"(d[55]), "+f"(d[56]), "+f"(d[57]), "+f"(d[58]), "+f"(d[59]), "+f"(d[60]), "+f"(d[61]), "+f"(d[62]), "+f"(d[63]), "+f"(d[64]), "+f"(d[65]), "+f"(d[66]), "+f"(d[67]), "+f"(d[68]), "+f"(d[69]), "+f"(d[70]), "+f"(d[71]), "+f"(d[72]), "+f"(d[73]), "+f"(d[74]), "+f"(d[75]), "+f"(d[76]), "+f"(d[77]), "+f"(d[78]), "+f"(d[79]), "+f"(d[80]), "+f"(d[81]), "+f"(d[82]), "+f"(d[83]), "+f"(d[84]), "+f"(d[85]), "+f"(d[86]), "+f"(d[87]), "+f"(d[88]), "+f"(d[89]), "+f"(d[90]), "+f"(d[91]), "+f"(d[92]), "+f"(d[93]), "+f"(d[94]), "+f"(d[95])
    : "r"(a0), "r"(a1), "r"(a2), "r"(a3), "l"(db), "r"(scale_d));
}

__device__ __forceinline__ uint32_t desc_lo(uint32_t addr, uint32_t lbo) { return ((addr & 0x3FFFF) >> 4) | ((lbo >> 4) << 16); }
template <uint32_t SBO>
__device__ __forceinline__ uint64_t desc64(uint32_t lo) {
  uint64_t d;
  asm("mov.b64 %0, {%1, %2};" : "=l"(d) : "r"(lo), "n"((SBO >> 4) | (1u << 30)));
  return d;
}
__device__ __forceinline__ void wg_fence() { asm volatile("wgmma.fence.sync.aligned;" ::: "memory"); }
__device__ __forceinline__ void wg_commit() { asm volatile("wgmma.commit_group.sync.aligned;" ::: "memory"); }
template <int N>
__device__ __forceinline__ void wg_wait() { asm volatile("wgmma.wait_group.sync.aligned %0;" ::"n"(N) : "memory"); }
__device__ __forceinline__ void bar_sync(int id) { asm volatile("bar.sync %0, 256;" ::"r"(id) : "memory"); }
__device__ __forceinline__ void bar_arrive(int id) { asm volatile("bar.arrive %0, 256;" ::"r"(id) : "memory"); }

template <int N>
__device__ __forceinline__ void pin(float (&r)[N]) {
#pragma unroll
  for (int i = 0; i < N; i++) asm volatile("" : "+f"(r[i])::"memory");
}
template <int N>
__device__ __forceinline__ void pin(uint32_t (&r)[N]) {
#pragma unroll
  for (int i = 0; i < N; i++) asm volatile("" : "+r"(r[i])::"memory");
}

__device__ __forceinline__ void mbar_init(uint32_t bar, uint32_t count) {
  asm volatile("mbarrier.init.shared::cta.b64 [%0], %1;" ::"r"(bar), "r"(count) : "memory");
}
__device__ __forceinline__ void mbar_expect_tx(uint32_t bar, uint32_t bytes) {
  asm volatile("mbarrier.arrive.expect_tx.shared::cta.b64 _, [%0], %1;" ::"r"(bar), "r"(bytes) : "memory");
}
__device__ __forceinline__ void mbar_arrive_local(uint32_t bar) {
  asm volatile("mbarrier.arrive.shared::cta.b64 _, [%0];" ::"r"(bar) : "memory");
}
__device__ __forceinline__ void mbar_arrive_cluster(uint32_t bar, uint32_t cta) {
  asm volatile(
      "{\n.reg .b32 ra;\nmapa.shared::cluster.u32 ra, %0, %1;\n"
      "mbarrier.arrive.shared::cluster.b64 _, [ra];\n}" ::"r"(bar),
      "r"(cta)
      : "memory");
}
__device__ __forceinline__ bool mbar_try(uint32_t bar, uint32_t parity) {
  uint32_t ok;
  asm volatile(
      "{\n.reg .pred p;\nmbarrier.try_wait.parity.shared::cta.b64 p, [%1], %2;\nselp.u32 %0, 1, 0, p;\n}"
      : "=r"(ok)
      : "r"(bar), "r"(parity)
      : "memory");
  return ok;
}
__device__ __forceinline__ uint32_t now_clk() {
  uint32_t t;
  asm volatile("mov.u32 %0, %%clock;" : "=r"(t));
  return t;
}
__device__ __forceinline__ void mbar_wait(uint32_t bar, uint32_t parity) {
  if (mbar_try(bar, parity)) return;
#pragma unroll 1
  for (int n = now_clk() & 1; n < kBarPolls; n++)
    if (mbar_try(bar, parity)) break;
}
__device__ __forceinline__ void mbar_spin(uint32_t bar, uint32_t parity) {
#pragma unroll 1
  for (int n = 0; n < kBarPolls; n++)
    if (mbar_try(bar, parity)) break;
}
__device__ __forceinline__ bool elect_one() {
  uint32_t r;
  asm volatile("{\n.reg .pred p;\nelect.sync _|p, 0xffffffff;\nselp.u32 %0, 1, 0, p;\n}" : "=r"(r));
  return r;
}
__device__ __forceinline__ void bulk_load(uint32_t dst, const void* src, uint32_t bytes, uint32_t bar) {
  asm volatile("cp.async.bulk.shared::cluster.global.mbarrier::complete_tx::bytes [%0], [%1], %2, [%3];" ::"r"(dst),
               "l"(src), "r"(bytes), "r"(bar)
               : "memory");
}
__device__ __forceinline__ void bulk_copy_peer(uint32_t addr, uint32_t bytes, uint32_t bar, uint32_t cta) {
  asm volatile(
      "{\n.reg .b32 ra, rb;\nmapa.shared::cluster.u32 ra, %0, %3;\nmapa.shared::cluster.u32 rb, %2, %3;\n"
      "cp.async.bulk.shared::cluster.shared::cta.mbarrier::complete_tx::bytes [ra], [%0], %1, [rb];\n}" ::"r"(addr),
      "r"(bytes), "r"(bar), "r"(cta)
      : "memory");
}
__device__ __forceinline__ void bulk_load_mc(uint32_t dst, const void* src, uint32_t bytes, uint32_t bar) {
  asm volatile(
      "cp.async.bulk.shared::cluster.global.mbarrier::complete_tx::bytes.multicast::cluster [%0], [%1], %2, [%3], "
      "%4;" ::"r"(dst),
      "l"(src), "r"(bytes), "r"(bar), "h"((uint16_t)3)
      : "memory");
}
constexpr uint64_t kEvictFirst = 0x12F0000000000000ull;
__device__ __forceinline__ void tma_load_2d(uint32_t dst, const CUtensorMap* map, int c0, int c1, uint32_t bar) {
  asm volatile(
      "cp.async.bulk.tensor.2d.shared::cluster.global.mbarrier::complete_tx::bytes.L2::cache_hint [%0], [%1, {%3, %4}], "
      "[%2], %5;" ::"r"(dst),
      "l"(map), "r"(bar), "r"(c0), "r"(c1), "l"(kEvictFirst)
      : "memory");
}
__device__ __forceinline__ void tma_store_2d(const CUtensorMap* map, uint32_t src, int c0, int c1) {
  asm volatile("cp.async.bulk.tensor.2d.global.shared::cta.bulk_group [%0, {%2, %3}], [%1];" ::"l"(map), "r"(src),
               "r"(c0), "r"(c1)
               : "memory");
}
__device__ __forceinline__ void cluster_arrive() { asm volatile("barrier.cluster.arrive.relaxed;" ::: "memory"); }
__device__ __forceinline__ void cluster_wait() { asm volatile("barrier.cluster.wait;" ::: "memory"); }
__device__ __forceinline__ float ex2(float x) {
  float y;
  asm("ex2.approx.ftz.f32 %0, %1;" : "=f"(y) : "f"(x));
  return y;
}
__device__ __forceinline__ uint32_t pack_bf16(float lo, float hi) {
  uint32_t r;
  asm("cvt.rn.bf16x2.f32 %0, %1, %2;" : "=r"(r) : "f"(hi), "f"(lo));
  return r;
}

__device__ __forceinline__ uint32_t pack_f16(float lo, float hi) {
  uint32_t r;
  asm("cvt.rn.f16x2.f32 %0, %1, %2;" : "=r"(r) : "f"(hi), "f"(lo));
  return r;
}

__device__ __forceinline__ uint32_t scale_f16(uint32_t w, float f) {
  float x, y;
  asm("{\n.reg .b16 a, b;\nmov.b32 {a, b}, %2;\ncvt.f32.f16 %0, a;\ncvt.f32.f16 %1, b;\n}" : "=f"(x), "=f"(y) : "r"(w));
  return pack_f16(x * f, y * f);
}

struct Params {
  const int* qk;
  const int* qv;
  const __nv_bfloat16* ks;
  const __nv_bfloat16* kz;
  const __nv_bfloat16* vs;
  const __nv_bfloat16* vz;
  const __nv_bfloat16* q;
  uint8_t* scratch;
  unsigned* flags;
  uint8_t* prob;
};

__device__ __forceinline__ int unit_row(int step, int grp, int mt) {
  return ((step >> 4) * 8 + grp) * kS + (step & 15) * kBN + mt * 8;
}
__device__ __forceinline__ uint8_t* tile_image(const Params& p, int step, int grp, int is_v) {
  return p.scratch + ((size_t)(grp * kRing + (unsigned)step % kRing) * 2 + is_v) * kTileBytes;
}
struct Unit { uint4 x[4]; uint2 s, z; };

__device__ __forceinline__ uint4 ldg128(const void* a) {
  uint4 v;
  asm volatile("ld.global.nc.L1::no_allocate.v4.u32 {%0, %1, %2, %3}, [%4];"
               : "=r"(v.x), "=r"(v.y), "=r"(v.z), "=r"(v.w)
               : "l"(a)
               : "memory");
  return v;
}
__device__ __forceinline__ uint4 ldg128_last_use(const void* a) {
  uint4 v;
  asm volatile("ld.global.nc.L1::no_allocate.L2::cache_hint.v4.u32 {%0, %1, %2, %3}, [%4], %5;"
               : "=r"(v.x), "=r"(v.y), "=r"(v.z), "=r"(v.w)
               : "l"(a), "l"(kEvictFirst)
               : "memory");
  return v;
}
__device__ __forceinline__ uint2 ldg64(const void* a) {
  uint2 v;
  asm volatile("ld.global.nc.L1::no_allocate.v2.u32 {%0, %1}, [%2];" : "=r"(v.x), "=r"(v.y) : "l"(a));
  return v;
}
__device__ __forceinline__ void stg64(uint64_t a, uint32_t x, uint32_t y) {
  asm volatile("st.global.L1::no_allocate.v2.u32 [%0], {%1, %2};" ::"l"(a), "r"(x), "r"(y) : "memory");
}
__device__ __forceinline__ uint32_t bf2_mul(uint32_t a, uint32_t b) {
  uint32_t r;
  asm("mul.rn.bf16x2 %0, %1, %2;" : "=r"(r) : "r"(a), "r"(b));
  return r;
}
__device__ __forceinline__ uint32_t bf2_fma(uint32_t a, uint32_t b, uint32_t c) {
  uint32_t r;
  asm("fma.rn.bf16x2 %0, %1, %2, %3;" : "=r"(r) : "r"(a), "r"(b), "r"(c));
  return r;
}
__device__ __forceinline__ uint32_t h2_fma(uint32_t a, uint32_t b, uint32_t c) {
  uint32_t r;
  asm("fma.rn.f16x2 %0, %1, %2, %3;" : "=r"(r) : "r"(a), "r"(b), "r"(c));
  return r;
}
__device__ __forceinline__ uint32_t h2_mul(uint32_t a, uint32_t b) {
  uint32_t r;
  asm("mul.rn.f16x2 %0, %1, %2;" : "=r"(r) : "r"(a), "r"(b));
  return r;
}
__device__ __forceinline__ float bf_lo(uint32_t w) { return __uint_as_float(w << 16); }
__device__ __forceinline__ float bf_hi(uint32_t w) { return __uint_as_float(w & 0xffff0000u); }
__device__ __forceinline__ uint32_t codes_bf16(uint32_t a, uint32_t b) { return pack_bf16((float)(int)a, (float)(int)b); }
__device__ __forceinline__ uint2 lds64(uint32_t a) {
  uint2 v;
  asm volatile("ld.shared.v2.u32 {%0, %1}, [%2];" : "=r"(v.x), "=r"(v.y) : "r"(a));
  return v;
}
__device__ __forceinline__ uint4 lds128(uint32_t a) {
  uint4 v;
  asm volatile("ld.shared.v4.u32 {%0, %1, %2, %3}, [%4];" : "=r"(v.x), "=r"(v.y), "=r"(v.z), "=r"(v.w) : "r"(a));
  return v;
}
__device__ __forceinline__ uint4 lds128v(uint32_t a) {
  uint4 v;
  asm volatile("ld.shared.v4.u32 {%0, %1, %2, %3}, [%4];" : "=r"(v.x), "=r"(v.y), "=r"(v.z), "=r"(v.w) : "r"(a) : "memory");
  return v;
}
__device__ __forceinline__ uint32_t k_scale(uint32_t s) { return bf2_fma(s, 0x40D540D5u, bf2_mul(s, 0x3BEE3BEEu)); }
__device__ __forceinline__ uint32_t k_zero(uint32_t z) { return bf2_mul(z, 0xBC80BC80u); }
__device__ __forceinline__ uint32_t k_pair(uint32_t x, uint32_t xs, uint32_t z, uint32_t s, uint32_t off) {
  return bf2_fma(bf2_fma(x, xs, z), s, off);
}
constexpr uint32_t kByteScaleK = 0x7F007F00u, kBf16ScaleK = 0x3C803C80u, kByteScaleV = 0x60006000u;
template <bool kIsV>
__device__ __forceinline__ void load_unit(const Params& p, int row0, uint32_t t, Unit& d) {
  const uint32_t hi = t >= 48 ? 1 : 0, q = t - hi * 48;
  const uint8_t* src = (const uint8_t*)((kIsV ? p.qv : p.qk) + (size_t)row0 * kD) + (hi * 3072 + q * 16);
#pragma unroll
  for (int i = 0; i < 4; i++) d.x[i] = ldg128_last_use(src + i * 768);
  if (kIsV) {
    uint32_t o = hi * 8;
    asm("" : "+r"(o));
    d.s = ldg64((const uint8_t*)(p.vs + row0) + o);
    d.z = ldg64((const uint8_t*)(p.vz + row0) + o);
  } else {
    d.s = ldg64((const uint8_t*)(p.ks + (row0 / kGroupTok) * kD) + q * 8);
    d.z = ldg64((const uint8_t*)(p.kz + (row0 / kGroupTok) * kD) + q * 8);
  }
}
__device__ __forceinline__ bool codes_are_bytes(const Unit& d, uint32_t a = 0) {
#pragma unroll
  for (int i = 0; i < 4; i++) a |= d.x[i].x | d.x[i].y | d.x[i].z | d.x[i].w;
  return !__any_sync(0xffffffffu, a > 255);
}
template <int kHalf>
__device__ __forceinline__ uint32_t dup16(uint32_t w) {
  uint32_t v;
  if (kHalf == 0) asm("{\n.reg .b16 a, b;\nmov.b32 {a, b}, %1;\nmov.b32 %0, {a, a};\n}" : "=r"(v) : "r"(w));
  else asm("{\n.reg .b16 a, b;\nmov.b32 {a, b}, %1;\nmov.b32 %0, {b, b};\n}" : "=r"(v) : "r"(w));
  return v;
}
template <bool kIsV>
__device__ __forceinline__ uint64_t unit_dst(const Params& p, int step, int grp, int mt, uint32_t t) {
  const uint32_t hi = t >= 48 ? 1 : 0, q = t - hi * 48;
  return (uint64_t)(tile_image(p, step, grp, kIsV && step < kOwn) + mt * (kIsV ? 3072 : 1024)) +
         ((q >> 4) * (kIsV ? 1024 : kChunkBytes) + hi * 512 + (q & 1) * 8 + ((((q & 15) >> 1) ^ (hi * 4)) << 4));
}
__device__ __forceinline__ void put64(uint64_t a, uint32_t x, uint32_t y) { stg64(a, x, y); }
__device__ __forceinline__ void put64(uint32_t a, uint32_t x, uint32_t y) {
  asm volatile("st.shared.v2.u32 [%0], {%1, %2};" ::"r"(a), "r"(x), "r"(y) : "memory");
}
template <typename Addr>
__device__ __forceinline__ void store_k(Addr dst, int slot, uint32_t t, const Unit& d, uint32_t bars, bool bytes) {
  const uint2 off = lds64(bars + kOffK + slot * (kD * 2) + (t >= 48 ? t - 48 : t) * 8);
  uint32_t x[8];
  if (bytes) {
#pragma unroll
    for (int i = 0; i < 4; i++) {
      x[2 * i] = d.x[i].y * 65536u + d.x[i].x;
      x[2 * i + 1] = d.x[i].w * 65536u + d.x[i].z;
    }
  } else {
#pragma unroll
    for (int i = 0; i < 4; i++) {
      x[2 * i] = codes_bf16(d.x[i].x, d.x[i].y);
      x[2 * i + 1] = codes_bf16(d.x[i].z, d.x[i].w);
    }
  }
  const uint32_t xs = bytes ? kByteScaleK : kBf16ScaleK;
  const uint32_t s0 = k_scale(d.s.x), s1 = k_scale(d.s.y), z0 = k_zero(d.z.x), z1 = k_zero(d.z.y);
#pragma unroll
  for (int i = 0; i < 4; i++)
    put64((dst ^ (i * 16)) + i * 128, k_pair(x[2 * i], xs, z0, s0, off.x), k_pair(x[2 * i + 1], xs, z1, s1, off.y));
}
constexpr uint32_t kCentreBits = 512 * 0x10001u;
constexpr float kCentre = 512 * (1.f / 16777216);
__device__ __forceinline__ void store_v(const Params& p, int step, int grp, int mt, uint32_t t, const Unit& d, uint32_t bars) {
  const uint64_t dst = unit_dst<true>(p, step, grp, mt, t);
  const uint2 par = lds64(bars + kParV + (step >> 4) * 32);
  const float alpha = __uint_as_float(par.x), centre = __uint_as_float(par.y ^ (step & 8) << 28);
#pragma unroll
  for (int i = 0; i < 4; i++) {
    const uint32_t zw = i < 2 ? d.z.x : d.z.y, sw = i < 2 ? d.s.x : d.s.y;
    const uint32_t zz = (i & 1) ? dup16<1>(zw) : dup16<0>(zw), ss = (i & 1) ? dup16<1>(sw) : dup16<0>(sw);
    auto pair = [&](uint32_t a, uint32_t b) {
      uint32_t v;
      asm("{\n.reg .b32 t;\nsub.rn.bf16x2 t, %1, %2;\nmul.rn.bf16x2 %0, t, %3;\n}"
          : "=r"(v)
          : "r"(codes_bf16(a, b)), "r"(zz), "r"(ss));
      return pack_f16(fmaf(bf_lo(v), alpha, centre), fmaf(bf_hi(v), alpha, centre));
    };
    stg64((dst ^ (i * 16)) + i * 128, pair(d.x[i].x, d.x[i].y), pair(d.x[i].z, d.x[i].w));
  }
}
__device__ __forceinline__ void store_v_any(const Params& p, int step, int grp, int mt, uint32_t t, const Unit& d, uint32_t bars) {
  const uint2 par = lds64(bars + kParV + (step >> 4) * 32 + 16);
  const uint32_t z0 = d.z.x - 0x40004000u, z1 = d.z.y - 0x40004000u;
  if (!codes_are_bytes(d, ((z0 | z1) & 0xFC00FC00u) | ((d.s.x | d.s.y) & 0x80008000u)) || par.x == 0) {
    store_v(p, step, grp, mt, t, d, bars);
    return;
  }
  const uint64_t dst = unit_dst<true>(p, step, grp, mt, t);
  const uint2 z = make_uint2(z0 * 8 + 0x84008400u, z1 * 8 + 0x84008400u);
  const uint2 s = make_uint2(h2_mul(d.s.x * 8 + par.y, par.x), h2_mul(d.s.y * 8 + par.y, par.x));
  const uint32_t c2 = kCentreBits ^ (step & 8) * 0x10001000u;
#pragma unroll
  for (int i = 0; i < 4; i++) {
    const uint32_t zw = i < 2 ? z.x : z.y, sw = i < 2 ? s.x : s.y;
    const uint32_t zz = (i & 1) ? dup16<1>(zw) : dup16<0>(zw), ss = (i & 1) ? dup16<1>(sw) : dup16<0>(sw);
    stg64((dst ^ (i * 16)) + i * 128, h2_fma(h2_fma(d.x[i].y * 65536u + d.x[i].x, kByteScaleV, zz), ss, c2),
          h2_fma(h2_fma(d.x[i].w * 65536u + d.x[i].z, kByteScaleV, zz), ss, c2));
  }
}
struct Stat { uint4 s[4], z[4]; };
struct Range { uint4 lo; uint32_t hi; };
__device__ __forceinline__ void stat_load(const Params& p, int head, int j, uint32_t lane, Stat& d) {
  const bool v = lane >= 24;
  const uint32_t off = v ? (head * kS + j * 256) * 2 + (lane - 24) * 16 : (head * 32 + j * 4) * (kD * 2) + lane * 16;
  const uint32_t step = v ? 128 : kD * 2;
  const uint8_t *ps = (const uint8_t*)(v ? p.vs : p.ks), *pz = (const uint8_t*)(v ? p.vz : p.kz);
#pragma unroll
  for (int i = 0; i < 4; i++) {
    uint32_t o = off + i * step;
    asm("" : "+r"(o));
    d.s[i] = ldg128(ps + o);
    d.z[i] = ldg128(pz + o);
  }
}
__device__ __forceinline__ uint32_t range2(uint32_t s, uint32_t z) {
  uint32_t r;
  asm("{\n.reg .b32 m;\nmax.xorsign.abs.bf16x2 m, %2, %3;\nmul.rn.bf16x2 %0, %1, m;\n}"
      : "=r"(r)
      : "r"(s), "r"(z), "r"(0x3F803F80u));
  return r & 0x7fff7fffu;
}
__device__ __forceinline__ void stat_add(const Stat& d, Range& r) {
  auto col = [&](uint32_t& lo, uint32_t a, uint32_t b, uint32_t c, uint32_t e) {
    lo = __vimin3_u16x2(__vimin3_u16x2(lo, a, b), c, e);
    r.hi = __vimax3_u16x2(__vimax3_u16x2(r.hi, a, b), c, e);
  };
  col(r.lo.x, range2(d.s[0].x, d.z[0].x), range2(d.s[1].x, d.z[1].x), range2(d.s[2].x, d.z[2].x), range2(d.s[3].x, d.z[3].x));
  col(r.lo.y, range2(d.s[0].y, d.z[0].y), range2(d.s[1].y, d.z[1].y), range2(d.s[2].y, d.z[2].y), range2(d.s[3].y, d.z[3].y));
  col(r.lo.z, range2(d.s[0].z, d.z[0].z), range2(d.s[1].z, d.z[1].z), range2(d.s[2].z, d.z[2].z), range2(d.s[3].z, d.z[3].z));
  col(r.lo.w, range2(d.s[0].w, d.z[0].w), range2(d.s[1].w, d.z[1].w), range2(d.s[2].w, d.z[2].w), range2(d.s[3].w, d.z[3].w));
}
__device__ __forceinline__ void sts128(uint32_t a, uint32_t x, uint32_t y, uint32_t z, uint32_t w) {
  asm volatile("st.shared.v4.u32 [%0], {%1, %2, %3, %4};" ::"r"(a), "r"(x), "r"(y), "r"(z), "r"(w) : "memory");
}
__device__ __forceinline__ uint4 stat_finish(const Range& r, uint32_t lane) {
  const bool v = lane >= 24;
  const uint32_t lo = __vimin3_u16x2(__vminu2(r.lo.x, r.lo.y), r.lo.z, r.lo.w);
  const float amin = bf_hi(__reduce_min_sync(0xffffffffu, v ? min(lo, lo << 16) : ~0u));
  const float amax = fmaxf(bf_hi(__reduce_max_sync(0xffffffffu, v ? max(r.hi, r.hi << 16) : 0u)), 1e-30f);
  const bool centred = amax <= 2.f * amin && amax <= 1e30f;
  const uint32_t a15 = __float_as_uint(__fdividef(centred ? 0.98f * kCentre * 32768 : 16.f * 32768, amax)) & 0xFFFFE000u;
  const float alpha = __uint_as_float(a15) * (1.f / 32768);
  if (lane == 24)
    return make_uint4(__float_as_uint(alpha), centred ? __float_as_uint(kCentre) : 0u, __float_as_uint(__fdividef(1.f, alpha)), 0u);
  if (v) return make_uint4(centred ? (0x3C00u | (a15 >> 13 & 0x3FFu)) * 0x10001u : 0u, ((a15 >> 23) - 239u) * 0x4000400u, 0u, 0u);
  return make_uint4(bf2_mul(r.lo.x, kOffsetFactor), bf2_mul(r.lo.y, kOffsetFactor), bf2_mul(r.lo.z, kOffsetFactor),
                    bf2_mul(r.lo.w, kOffsetFactor));
}
__device__ __forceinline__ void stat_keep(const uint4& x, int wave, uint32_t lane, uint32_t bars) {
  if (lane < 26)
    sts128(bars + lane * 16 + (lane < 24 ? kOffK + (wave & 1) * (kD * 2) : kParV - 24 * 16 + wave * 32), x.x, x.y, x.z, x.w);
}
__device__ __forceinline__ void prefetch_bulk(const void* g, uint32_t bytes) {
  asm volatile("cp.async.bulk.prefetch.L2.global [%0], %1;" ::"l"(g), "r"(bytes) : "memory");
}
__device__ __forceinline__ void publish(const Params& p, int flag, int grp) {
  __syncwarp();
  asm volatile(
      "{\n.reg .pred p;\nelect.sync _|p, 0xffffffff;\n@p red.release.gpu.global.add.u32 [%0], 1;\n}" ::"l"(
          p.flags + grp * kFlagsPerGroup + flag)
      : "memory");
}
__device__ __forceinline__ void flag_wait(const unsigned* f) {
#pragma unroll 1
  for (int n = 0; n < kFlagPolls; n++) {
    unsigned v;
    asm volatile("ld.acquire.gpu.global.u32 %0, [%1];" : "=r"(v) : "l"(f) : "memory");
    if (__all_sync(0xffffffffu, v >= kFlagTarget)) break;
  }
  asm volatile("fence.proxy.async.global;" ::: "memory");
}

__device__ __forceinline__ void helper_cta(const Params& p, const CUtensorMap& tmq, uint32_t sbase, uint32_t t_start) {
  constexpr int kFullQ = 0, kEmptyQ = 32, kDone = 64, kFullK = 72;
  const uint32_t bars = sbase + kSmemBar, sq = sbase + 2 * kTileBytes;
  const int warp = __shfl_sync(0xffffffffu, threadIdx.x >> 5, 0);
  const int lane = threadIdx.x & 31;
  const int grp0 = blockIdx.x - kOwners;
  auto job_row = [&](int n) { return ((kWaves - 1) * 8 + n * kHelpers + grp0) * kS; };
  auto job_images = [&](int n) { return p.prob + (size_t)(kHelperImages + (n * kHelpers + grp0) * (kTail * kTileBytes)); };
  if (threadIdx.x == 0) {
    for (int i = 0; i < 4; i++) {
      mbar_init(bars + kFullQ + 8 * i, 1);
      mbar_init(bars + kEmptyQ + 8 * i, 4);
    }
    mbar_init(bars + kDone, 8);
    mbar_init(bars + kFullK, 1);
    asm volatile("fence.proxy.async.shared::cta;" ::: "memory");
  }
  auto sleep_until = [&](uint32_t t) {
    while (now_clk() - t_start < t) __nanosleep(200);
  };
  auto wait_long = [&](uint32_t bar, uint32_t parity) {
#pragma unroll 1
    for (int k = 0; k < kFlagPolls && !mbar_try(bar, parity); k++) __nanosleep(200);
  };
  sleep_until(kHelperPrepare);
  if (warp < 6) {
    const int head = job_row(warp & 1) / kS - (warp >> 1) * 8;
    if (warp < 2 && elect_one()) prefetch_bulk(p.qk + (size_t)(head * kS + kS - kTail * kBN) * kD, kTail * 2 * kTileBytes);
    __syncwarp();
    Range r = {make_uint4(~0u, ~0u, ~0u, ~0u), 0u};
#pragma unroll 1
    for (int j = 0; j < 8; j += 2) {
      Stat a, b;
      stat_load(p, head, j, lane, a);
      stat_load(p, head, j + 1, lane, b);
      stat_add(a, r);
      stat_add(b, r);
    }
    const uint4 x = stat_finish(r, lane);
    if (warp < 2) stat_keep(x, warp, lane, bars);
    *(uint4*)(p.prob + kHeadStats + head * 512 + lane * 16) = x;
  }
  __syncthreads();
  if (threadIdx.x < 2)
    asm volatile("red.release.gpu.global.add.u32 [%0], %1;" ::"l"(p.flags + kFlagStats + threadIdx.x * kHelpers + grp0),
                 "n"(kFlagTarget)
                 : "memory");
  {
    const int team = warp / 3, n = team >> 1;
    const uint32_t t = threadIdx.x - team * 96, hi = t >= 48 ? 1 : 0, q = t - hi * 48;
    const int row = job_row(n) + kS - kTail * kBN;
    const uint64_t dst = (uint64_t)job_images(n) +
                         ((q >> 4) * kChunkBytes + hi * 512 + (q & 1) * 8 + ((((q & 15) >> 1) ^ (hi * 4)) << 4));
    auto unit_at = [&](int m) { return (m >> 4) * kTileBytes + (m & 15) * 1024; };
    Unit a, b;
    load_unit<false>(p, row + (team & 1) * 8, t, a);
#pragma unroll 1
    for (int m = team & 1; m < 16 * kTail; m += 4) {
      load_unit<false>(p, row + (m + 2) * 8, t, b);
      store_k(dst + unit_at(m), n, t, a, bars, codes_are_bytes(a));
      load_unit<false>(p, row + min(m + 4, 16 * kTail - 1) * 8, t, a);
      store_k(dst + unit_at(m + 2), n, t, b, bars, codes_are_bytes(b));
    }
    __threadfence();
  }
  __syncthreads();
  if (warp >= 8) {
    asm volatile("setmaxnreg.dec.sync.aligned.u32 104;");
    if (warp == 8) {
      sleep_until(kHelperDelay);
#pragma unroll 1
      for (int u = 0; u < 32; u++) {
        if ((u & 15) == (u < 16 ? 0 : 2)) {
          if (u > 0) mbar_spin(bars + kDone, 0);
          asm volatile("fence.proxy.async.global;" ::: "memory");
          if (elect_one()) {
            mbar_expect_tx(bars + kFullK, kTail * kTileBytes);
            bulk_load(sbase, job_images(u >> 4), kTail * kTileBytes, bars + kFullK);
          }
          __syncwarp();
        }
        const int row = job_row(u >> 4) + (u & 15) * 128;
#pragma unroll 1
        for (int w = 0; w < 2; w++) {
          const uint32_t slot = w * 2 + (u & 1), bar = bars + kFullQ + 8 * slot;
          mbar_spin(bars + kEmptyQ + 8 * slot, ((u >> 1) & 1) ^ 1);
          if (elect_one()) {
            mbar_expect_tx(bar, kTileBytes / 2);
#pragma unroll
            for (int c = 0; c < 3; c++)
              tma_load_2d(sq + slot * (kTileBytes / 2) + c * 8192, &tmq, c * 64, row + w * 64, bar);
          }
          __syncwarp();
        }
        if (u == 12 && elect_one()) prefetch_bulk(job_images(1), kTail * kTileBytes);
        __syncwarp();
        const int v = min(u + 3, 31);
        if (elect_one()) prefetch_bulk(p.q + (size_t)(job_row(v >> 4) + (v & 15) * 128) * kD, kTileBytes);
        __syncwarp();
      }
    } else {
      if (warp == 9) {
#pragma unroll 1
        for (int n = 0; n < 2; n++) {
          wait_long(bars + kDone, n);
          if (elect_one()) {
            asm volatile("red.release.gpu.global.add.u32 [%0], %1;" ::"l"(p.flags + kFlagHelper + n * kHelpers + grp0),
                         "n"(kFlagTarget)
                         : "memory");
          }
          __syncwarp();
        }
      }
    }
    return;
  }
  asm volatile("setmaxnreg.inc.sync.aligned.u32 200;");
  const int wg = warp >> 2;
  float A[64], B[64];
#pragma unroll
  for (int i = 0; i < 64; i++) asm volatile("" : "=f"(A[i]), "=f"(B[i]));
  auto issue = [&](float (&S)[64], int u, int j) {
    const uint32_t slot = wg * 2 + (u & 1);
    if (j == 0) mbar_wait(bars + kFullQ + 8 * slot, (u >> 1) & 1);
    const uint32_t kb = desc_lo(sbase, 16) + j * (kTileBytes >> 4);
    const uint32_t qb = desc_lo(sq, 16) + slot * (kTileBytes >> 5);
    pin(S);
    wg_fence();
#pragma unroll
    for (int kk = 0; kk < 12; kk++)
      wgmma_ss_n128(S, desc64<1024>(qb + (kk >> 2) * 512 + (kk & 3) * 2), desc64<1024>(kb + (kk >> 2) * 1024 + (kk & 3) * 2), kk > 0);
    wg_commit();
  };
  float d[4], l[4];
  bool shifted;
  auto finish = [&](float (&S)[64], int u, int j) {
    pin(S);
    int a0 = 0, a1 = 0;
    uint32_t u0 = ~0u, u1 = ~0u;
#pragma unroll
    for (int i = 0; i < 64; i += 4) {
      a0 = __vimax3_s32(a0, __float_as_int(S[i]), __float_as_int(S[i + 1]));
      a1 = __vimax3_s32(a1, __float_as_int(S[i + 2]), __float_as_int(S[i + 3]));
      if (i < 16) {
        u0 = __vimin3_u32(u0, __float_as_uint(S[i]), __float_as_uint(S[i + 1]));
        u1 = __vimin3_u32(u1, __float_as_uint(S[i + 2]), __float_as_uint(S[i + 3]));
      }
    }
    uint8_t* tile = p.prob + (size_t)((((u >> 4) * kHelpers + grp0) * 16 + (u & 15)) * kProbBytes);
    float d0 = 0.f, d1 = 0.f;
    if (j == 0) shifted = false;
    if (__any_sync(0xffffffffu, max(a0, a1) > __float_as_int(kLazyAbove) || max(u0, u1) >= __float_as_uint(-kLazyBelow))) {
      shifted = true;
      d0 = S[0];
      d1 = S[2];
#pragma unroll
      for (int i = 0; i < 64; i += 4) {
        d0 = fmaxf(d0, fmaxf(S[i], S[i + 1]));
        d1 = fmaxf(d1, fmaxf(S[i + 2], S[i + 3]));
      }
      d0 = fmaxf(d0, __shfl_xor_sync(0xffffffffu, d0, 1));
      d1 = fmaxf(d1, __shfl_xor_sync(0xffffffffu, d1, 1));
      d0 = fmaxf(d0, __shfl_xor_sync(0xffffffffu, d0, 2));
      d1 = fmaxf(d1, __shfl_xor_sync(0xffffffffu, d1, 2));
#pragma unroll
      for (int i = 0; i < 64; i++) S[i] -= (i & 2) ? d1 : d0;
    }
    float l0 = 0.f, l1 = 0.f;
#pragma unroll
    for (int i = 0; i < 64; i += 4) {
#pragma unroll
      for (int k = 0; k < 4; k++) S[i + k] = ex2(S[i + k]);
      l0 += S[i] + S[i + 1];
      l1 += S[i + 2] + S[i + 3];
      if (j == 0 && i == 48 - 4) {
        pin(S);
        asm volatile("st.volatile.shared.f32 [%0], %1;" ::"r"(bars + kDummy), "f"(l0 + l1) : "memory");
        wg_wait<0>();
        if (lane == 0) mbar_arrive_local(bars + kEmptyQ + 8 * (wg * 2 + (u & 1)));
      }
    }
    pin(S);
    l0 += __shfl_xor_sync(0xffffffffu, l0, 1);
    l1 += __shfl_xor_sync(0xffffffffu, l1, 1);
    l0 += __shfl_xor_sync(0xffffffffu, l0, 2);
    l1 += __shfl_xor_sync(0xffffffffu, l1, 2);
    uint8_t* dst = tile + (2 * j + wg) * 16384 + (threadIdx.x & 127) * 16;
#pragma unroll
    for (int i = 0; i < 8; i++)
      asm volatile("st.global.L1::no_allocate.v4.u32 [%0], {%1, %2, %3, %4};" ::"l"(dst + i * 2048),
                   "r"(pack_f16(S[8 * i], S[8 * i + 1])), "r"(pack_f16(S[8 * i + 2], S[8 * i + 3])),
                   "r"(pack_f16(S[8 * i + 4], S[8 * i + 5])), "r"(pack_f16(S[8 * i + 6], S[8 * i + 7]))
                   : "memory");
    d[2 * j] = d0;
    d[2 * j + 1] = d1;
    l[2 * j] = 0.25f * l0;
    l[2 * j + 1] = 0.25f * l1;
    if (j == 1 && (lane & 3) == 0) {
      if (shifted) {
        float4* extra = (float4*)(tile + kProbExtra + threadIdx.x * 8);
        extra[0] = make_float4(d[0], d[1], d[2], d[3]);
        extra[1] = make_float4(l[0], l[1], l[2], l[3]);
      }
      stg64((uint64_t)(tile + kProbSums + threadIdx.x * 2), __float_as_uint(shifted ? -1.f : l[0] + l[2]),
            __float_as_uint(l[1] + l[3]));
    }
  };
  if (wg == 1) bar_arrive(2);
#pragma unroll 1
  for (int n = 0; n < 2; n++) {
    wait_long(bars + kFullK, n);
#pragma unroll 1
    for (int u = 16 * n; u < 16 * n + 16; u++) {
      bar_sync(2 + wg);
      issue(A, u, 0);
      issue(B, u, 1);
      bar_arrive(3 - wg);
      wg_wait<1>();
      finish(A, u, 0);
      finish(B, u, 1);
    }
    __syncwarp();
    if (lane == 0) mbar_arrive_local(bars + kDone);
  }
}

__global__ void __cluster_dims__(2, 1, 1) __launch_bounds__(384, 1)
    attn_kernel(const Params p, const __grid_constant__ CUtensorMap tmq, const __grid_constant__ CUtensorMap tmo) {
  extern __shared__ uint8_t smem_raw[];
  const uint32_t t_start = now_clk();
  const uint32_t sbase = ((uint32_t)__cvta_generic_to_shared(smem_raw) + 1023) & ~1023u;
  if (blockIdx.x >= kOwners) {
    helper_cta(p, tmq, sbase, t_start);
    return;
  }
  const uint32_t bars = sbase + kSmemBar;
  const int grp = blockIdx.x >> 4, mt = blockIdx.x & 15;
  const int warp = __shfl_sync(0xffffffffu, threadIdx.x >> 5, 0);
  const int lane = threadIdx.x & 31;

  auto load_q = [&](int tile, int w) {
    const uint32_t bar = bars + kBarFullQ + 8 * w;
    const int row = (tile * 8 + grp) * kS + mt * 128 + w * 64;
    mbar_expect_tx(bar, 16384);
    mbar_expect_tx(bars + kBarFullQ2 + 8 * w, 8192);
#pragma unroll
    for (int c = 0; c < 3; c++)
      tma_load_2d(sbase + kSmemQ + w * 24576 + c * 8192, &tmq, c * 64, row, c < 2 ? bar : bars + kBarFullQ2 + 8 * w);
  };
  if (warp == 8 && elect_one()) {
    mbar_init(bars + kBarParams, 1);
    mbar_init(bars + kBarCodes, 1);
    mbar_init(bars + kBarUnits, 1);
    asm volatile("fence.proxy.async.shared::cta;" ::: "memory");
    mbar_expect_tx(bars + kBarParams, 32768);
    bulk_load(sbase + kSmemV, p.ks + grp * 32 * kD, 12288, bars + kBarParams);
    bulk_load(sbase + kSmemV + 12288, p.kz + grp * 32 * kD, 12288, bars + kBarParams);
    bulk_load(sbase + kSmemV + 24576, p.vs + grp * kS, 4096, bars + kBarParams);
    bulk_load(sbase + kSmemV + 36864, p.vz + grp * kS, 4096, bars + kBarParams);
  }
  __syncwarp();
  if (warp == 8) {
    asm volatile("bar.arrive 6, 160;" ::: "memory");
    while (now_clk() - t_start < grp * kGroupStagger) {}
  }
  const int row_k0 = grp * kS + (blockIdx.x & 1) * 64;
  if (warp == 8 && elect_one()) {
    mbar_expect_tx(bars + kBarUnits, 4 * 6144);
#pragma unroll
    for (int j = 0; j < 4; j++)
      bulk_load(sbase + kSmemK + 3 * kChunkBytes + j * 6144,
                (j & 1 ? p.qv : p.qk) + (size_t)unit_row((j >> 1) + 1 - (j & 1), grp, mt) * kD, 6144, bars + kBarUnits);
    mbar_expect_tx(bars + kBarCodes, kTileBytes);
    bulk_load(sbase + kSmemV + kTileBytes, p.qk + (size_t)row_k0 * kD, kTileBytes, bars + kBarCodes);
    for (int i = 0; i < 2; i++) {
      mbar_init(bars + kBarFullK01 + 8 * i, 1);
      mbar_init(bars + kBarFullV + 8 * i, 1);
      mbar_init(bars + kBarEmptyK12 + 8 * i, 16);
      mbar_init(bars + kBarEmptyV + 8 * i, 16);
      mbar_init(bars + kBarFullQ + 8 * i, 1);
      mbar_init(bars + kBarFullQ2 + 8 * i, 1);
      mbar_init(bars + kBarEmptyQ + 8 * i, 4);
      mbar_init(bars + kBarStage + 8 * i, 4);
      mbar_init(bars + kBarStaged + 8 * i, 4);
      for (int c = 0; c < 3; c++) mbar_init(bars + kBarTail + 24 * i + 8 * c, 4);
    }
    mbar_init(bars + kBarFullK2, 1);
    mbar_init(bars + kBarFullV2, 1);
    mbar_init(bars + kBarEmptyK0, 16);
    asm volatile("st.shared.u32 [%0], %1;" ::"r"(bars + kProgress), "r"(0) : "memory");
    asm volatile("fence.mbarrier_init.release.cluster;" ::: "memory");
    asm volatile("fence.acq_rel.cta;" ::: "memory");
    asm volatile("prefetch.tensormap [%0];" ::"l"(&tmq) : "memory");
  }
  __syncwarp();
  cluster_arrive();
  const bool helper = warp > 8 || (warp >= 4 && warp < 7);
  const uint32_t th = warp < 8 ? threadIdx.x & 127 : threadIdx.x - 288;
  const int it = warp < 8 ? 1 : 0;
  if (warp == 8) {
    while (now_clk() - t_start < kQDelay + grp * kQStagger) {}
#pragma unroll 1
    for (int w = 0; w < 2; w++)
      if (elect_one()) load_q(0, w);
  }
  __syncwarp();
  if (warp < 4) {
    asm volatile("bar.sync 6, 160;" ::: "memory");
    Range r = {make_uint4(~0u, ~0u, ~0u, ~0u), 0u};
    mbar_spin(bars + kBarParams, 0);
    const uint32_t pitch = lane >= 24 ? 128 : kD * 2;
    uint32_t src = sbase + kSmemV + (lane >= 24 ? 24576 - 384 : 0) + lane * 16 + warp * 8 * pitch;
#pragma unroll 1
    for (int j = 0; j < 2; j++) {
      Stat st;
#pragma unroll
      for (int i = 0; i < 4; i++, src += pitch) {
        st.s[i] = lds128(src);
        st.z[i] = lds128(src + 12288);
      }
      stat_add(st, r);
    }
    const uint32_t part = sbase + kSmemV + 40960 + lane * 16;
    sts128(part + warp * 1024, r.lo.x, r.lo.y, r.lo.z, r.lo.w);
    sts128(part + warp * 1024 + 512, r.hi, 0u, 0u, 0u);
    asm volatile("bar.sync 4, 128;" ::: "memory");
#pragma unroll
    for (int j = 1; j < 4; j++) {
      const uint32_t other = part + ((warp + j) & 3) * 1024;
      const uint4 lo = lds128(other);
      r.lo = make_uint4(__vminu2(r.lo.x, lo.x), __vminu2(r.lo.y, lo.y), __vminu2(r.lo.z, lo.z), __vminu2(r.lo.w, lo.w));
      r.hi = __vmaxu2(r.hi, lds64(other + 512).x);
    }
    stat_keep(stat_finish(r, lane), 0, lane, bars);
    __syncwarp();
    if (warp == 0) asm volatile("bar.arrive 5, 224;" ::: "memory");
  }
  if (helper) {
    asm volatile("bar.sync 5, 224;" ::: "memory");
    const uint32_t hi = th >= 48 ? 1 : 0, q = th - hi * 48;
    const uint32_t src = sbase + kSmemK + 3 * kChunkBytes + it * 12288 + hi * 3072 + q * 16;
    const uint32_t kp = sbase + kSmemV + (2 * it + 2 + (mt >> 3)) * (kD * 2) + q * 8;
    const uint32_t vp = sbase + kSmemV + 24576 + (it * kBN + mt * 8 + hi * 4) * 2;
    Unit k0, v0;
    k0.s = lds64(kp);
    k0.z = lds64(kp + 12288);
    v0.s = lds64(vp);
    v0.z = lds64(vp + 12288);
    mbar_spin(bars + kBarUnits, 0);
#pragma unroll
    for (int i = 0; i < 4; i++) {
      k0.x[i] = lds128(src + i * 768);
      v0.x[i] = lds128(src + 6144 + i * 768);
    }
    store_k(unit_dst<false>(p, it + 1, grp, mt, th), 0, th, k0, bars, false);
    store_v(p, it, grp, mt, th, v0, bars);
    if (warp < 8) asm volatile("bar.arrive 3, 192;" ::: "memory");
  }
  cluster_wait();
  if (warp < 4) {
    uint2 o0[3], s0[3], z0[3];
#pragma unroll
    for (int c = 0; c < 3; c++) {
      const uint32_t col = c * 128 + (threadIdx.x & 15) * 8;
      o0[c] = lds64(bars + kOffK + col);
      s0[c] = lds64(sbase + kSmemV + (blockIdx.x & 1) * (kD * 2) + col);
      z0[c] = lds64(sbase + kSmemV + 12288 + (blockIdx.x & 1) * (kD * 2) + col);
      s0[c] = make_uint2(k_scale(s0[c].x), k_scale(s0[c].y));
      z0[c] = make_uint2(k_zero(z0[c].x), k_zero(z0[c].y));
    }
    mbar_spin(bars + kBarCodes, 0);
    const uint32_t r = threadIdx.x >> 4, half = sbase + kSmemK + (blockIdx.x & 1) * (kChunkBytes / 2);
    uint32_t src = sbase + kSmemV + kTileBytes + r * 768 + (threadIdx.x & 15) * 16;
    uint32_t dst = half + r * 128 + (threadIdx.x & 1) * 8 + ((((threadIdx.x & 15) >> 1) ^ r) << 4);
#pragma unroll 1
    for (int i = 0; i < 4; i++, src += 16 * 768, dst += 2048) {
      uint4 x[6];
#pragma unroll
      for (int j = 0; j < 6; j++)
        asm volatile("ld.shared.v4.u32 {%0, %1, %2, %3}, [%4];"
                     : "=r"(x[j].x), "=r"(x[j].y), "=r"(x[j].z), "=r"(x[j].w)
                     : "r"(src + (j & 1) * 8 * 768 + (j >> 1) * 256));
#pragma unroll
      for (int j = 0; j < 6; j++)
        asm volatile("st.shared.v2.u32 [%0], {%1, %2};" ::"r"(dst + (j & 1) * 1024 + (j >> 1) * kChunkBytes),
                     "r"(k_pair(codes_bf16(x[j].x, x[j].y), kBf16ScaleK, z0[j >> 1].x, s0[j >> 1].x, o0[j >> 1].x)),
                     "r"(k_pair(codes_bf16(x[j].z, x[j].w), kBf16ScaleK, z0[j >> 1].y, s0[j >> 1].y, o0[j >> 1].y)));
    }
    asm volatile("fence.proxy.async.shared::cta;" ::: "memory");
    asm volatile("bar.sync 4, 128;" ::: "memory");
    if (threadIdx.x == 0) {
      mbar_expect_tx(bars + kBarFullK01, kChunkBytes);
      mbar_expect_tx(bars + kBarFullK2, kChunkBytes / 2);
#pragma unroll
      for (int c = 0; c < 3; c++)
        bulk_copy_peer(half + c * kChunkBytes, kChunkBytes / 2, bars + (c < 2 ? kBarFullK01 : kBarFullK2),
                       (blockIdx.x & 1) ^ 1);
    }
  }

  if (warp >= 8) {
    asm volatile("setmaxnreg.dec.sync.aligned.u32 56;");
    if (warp == 8) {
      const uint32_t rank = blockIdx.x & 1;
      const unsigned* flags = p.flags + grp * kFlagsPerGroup;
      const uint8_t* const images = tile_image(p, 0, grp, 0);
      auto image = [&](int step, uint32_t offset) { return images + ((step & (kRing - 1)) * (2 * kTileBytes) + offset); };
      uint32_t k_dst = sbase + kSmemK + 2 * kChunkBytes + rank * (kChunkBytes / 2);
      auto next_slot = [&]() {
        k_dst += kChunkBytes;
        if (k_dst >= sbase + kSmemV) k_dst -= 5 * kChunkBytes;
        return k_dst;
      };
      auto k_chunk = [&](uint32_t dst, int step, int c, uint32_t bar) {
        bulk_load_mc(dst, image(step, c * kChunkBytes + rank * (kChunkBytes / 2)), kChunkBytes / 2, bar);
      };
      auto load_k01 = [&](int step) {
        const uint32_t bar = bars + kBarFullK01 + 8 * (step & 1);
        const uint32_t d0 = next_slot(), d1 = next_slot();
        if (elect_one()) {
          mbar_expect_tx(bar, 2 * kChunkBytes);
          k_chunk(d0, step, 0, bar);
          k_chunk(d1, step, 1, bar);
        }
        __syncwarp();
      };
      auto load_k2 = [&](int step) {
        const uint32_t d = next_slot();
        if (elect_one()) {
          mbar_expect_tx(bars + kBarFullK2, kChunkBytes);
          k_chunk(d, step, 2, bars + kBarFullK2);
        }
        __syncwarp();
      };
      auto v_part = [&](int step, uint32_t len, uint32_t bar) {
        bulk_load_mc(sbase + kSmemV + (step & 1) * kTileBytes + rank * (len / 2),
                     image(step, kTileBytes + rank * (len / 2)), len / 2, bar);
      };
      auto load_vt = [&](int step) {
        const uint32_t bar = bars + kBarFullV + 8 * (step & 1);
        if (elect_one()) {
          mbar_expect_tx(bar, kTileBytes);
          v_part(step, kTileBytes, bar);
        }
        __syncwarp();
      };
      auto wait_flag = [&](int f) {
        flag_wait(flags + f);
      };
      auto store_out = [&](int tile, int w) {
        mbar_spin(bars + kBarStaged + 8 * w, tile & 1);
        asm volatile("fence.proxy.async.shared::cta;" ::: "memory");
        if (elect_one()) {
          const int row = (tile * 8 + grp) * kS + mt * 128 + w * 64;
#pragma unroll
          for (int c = 0; c < 3; c++)
            tma_store_2d(&tmo, sbase + kSmemV + w * kTileBytes + kTileBytes / 2 + c * 8192, c * 64, row);
          asm volatile("cp.async.bulk.commit_group;" ::: "memory");
        }
        __syncwarp();
      };
      auto reload_v = [&](int w, int step, uint32_t bar) {
        asm volatile("cp.async.bulk.wait_group.read 0;" ::: "memory");
        if (elect_one())
          bulk_load(sbase + kSmemV + w * kTileBytes + kTileBytes / 2, image(step, kTileBytes + kTileBytes / 2), kTileBytes / 2, bar);
        __syncwarp();
      };
      int pf = 3;
      uint32_t pf_at = unit_row(pf, grp, mt) * (kD * 4);
      auto prefetch_next = [&]() {
        const uint32_t at = pf_at;
        pf++;
        pf_at += (pf & 15) ? kBN * kD * 4 : (kBN + 7 * kS) * kD * 4;
        if (elect_one()) {
          prefetch_bulk((const uint8_t*)p.qv + at, 6144);
          if (pf < kOwn) prefetch_bulk((const uint8_t*)p.qk + pf_at, 6144);
        }
        __syncwarp();
      };
      const uint8_t* prob = p.prob + (size_t)(blockIdx.x * kProbBytes);
      constexpr int kPollStep = (kOwn - 3) | 1;
      auto load_p = [&](int j, int w, uint32_t bar) {
        bulk_load(sbase + kSmemK + slot_p(j, w) * kChunkBytes, prob + (2 * j + w) * kChunkBytes, kChunkBytes, bar);
      };
      wait_flag(1);
      load_k01(1);
#pragma unroll 1
      for (int s = 0; s < kOwn - 1; s++) {
        const bool newq = (s & 15) == 15;
        if (newq) {
          mbar_spin(bars + kBarEmptyQ, (s >> 4) & 1);
          if (elect_one()) load_q((s >> 4) + 1, 0);
          __syncwarp();
        }
        mbar_spin(bars + kBarEmptyK0, s & 1);
        load_k2(s + 1);
        if (s == 0) {
          if (elect_one()) {
            mbar_expect_tx(bars + kBarFullV, kTileBytes / 2);
            mbar_expect_tx(bars + kBarFullV2, kTileBytes / 2);
            v_part(0, kTileBytes / 2, bars + kBarFullV);
            bulk_load_mc(sbase + kSmemV + kTileBytes / 2 + rank * (kTileBytes / 4),
                         image(0, kTileBytes + kTileBytes / 2 + rank * (kTileBytes / 4)), kTileBytes / 4,
                         bars + kBarFullV2);
          }
          __syncwarp();
          prefetch_next();
        }
        const bool tile_end = (s & 15) == 0 && s > 0;
        if (tile_end) {
          store_out((s >> 4) - 1, 0);
          reload_v(0, s, bars + kBarFullV2);
        }
        const int pf_end = min(s + kLead + 2 + (s >= kOwn - 7), kSteps - 1);
        if (pf < pf_end) prefetch_next();
        if (newq) {
          mbar_spin(bars + kBarEmptyQ + 8, (s >> 4) & 1);
          if (elect_one()) load_q((s >> 4) + 1, 1);
          __syncwarp();
        }
        if (s & 1) {
          int f = grp * kFlagsPerGroup + s + 2;
          if (lane == 31 && s == kStatStep) f = kFlagStats + grp;
          if (lane == 31 && s == kPollStep) f = kFlagHelper + grp;
          flag_wait(p.flags + f);
        }
        if (s == kPollStep && elect_one()) prefetch_bulk(prob, kProbExtra);
        __syncwarp();
        mbar_spin(bars + kBarEmptyK12 + 8 * (s & 1), (s >> 1) & 1);
        if (s + 2 < kOwn) load_k01(s + 2);
        else if (elect_one()) {
          mbar_expect_tx(bars + kBarUnits, 2 * kChunkBytes + 512);
          bulk_load(bars + kOffK, prob + kProbSums, 512, bars + kBarUnits);
          load_p(0, 0, bars + kBarUnits);
          load_p(0, 1, bars + kBarUnits);
        }
        __syncwarp();
        mbar_spin(bars + kBarEmptyV + 8 * ((s + 1) & 1), (((s + 1) >> 1) & 1) ^ 1);
        if (newq || tile_end) {
          const uint32_t bar = bars + kBarFullV + 8 * ((s + 1) & 1);
          if (elect_one()) {
            mbar_expect_tx(bar, newq ? kTileBytes / 2 : kTileBytes);
            if (newq) mbar_expect_tx(bars + kBarFullV2, kTileBytes / 2);
            v_part(s + 1, kTileBytes / 2, bar);
          }
          __syncwarp();
          if (tile_end) {
            store_out((s >> 4) - 1, 1);
            reload_v(1, s + 1, bar);
          }
        } else {
          load_vt(s + 1);
        }
        if ((s & 15) == kStatStep && s < kSteps - 16) {
          uint4 x;
          asm volatile("ld.global.L1::no_allocate.v4.u32 {%0, %1, %2, %3}, [%4];"
                       : "=r"(x.x), "=r"(x.y), "=r"(x.z), "=r"(x.w)
                       : "l"(p.prob + (kHeadStats + (((s >> 4) + 1) * 8 + grp) * 512 + lane * 16))
                       : "memory");
          stat_keep(x, (s >> 4) + 1, lane, bars);
          __syncwarp();
        }
        asm volatile("st.volatile.shared.u32 [%0], %1;" ::"r"(bars + kProgress), "r"(s + 1) : "memory");
        if (pf <= pf_end && !tile_end) prefetch_next();
        if (s < kSteps - 16) {
          if ((s & 12) == 8) {
            const uint8_t* qn = (const uint8_t*)(p.q + (size_t)((((s >> 4) + 1) * 8 + grp) * kS + mt * 128) * kD);
            if (elect_one()) prefetch_bulk(qn + (s & 3) * 12288, 12288);
            __syncwarp();
          }
        }
      }
      wait_flag(kSteps - 1);
      mbar_spin(bars + kBarEmptyK12 + 8 * ((kOwn - 1) & 1), ((kOwn - 1) >> 1) & 1);
      if (elect_one()) {
        mbar_expect_tx(bars + kBarFullQ, kTileBytes);
        bulk_load_mc(sbase + kSmemQ + rank * (kTileBytes / 2), image(kOwn, rank * (kTileBytes / 2)),
                     kTileBytes / 2, bars + kBarFullQ);
        mbar_expect_tx(bars + kBarCodes, kChunkBytes);
        load_p(1, 0, bars + kBarCodes);
      }
      __syncwarp();
      mbar_spin(bars + kBarEmptyV, ((kOwn >> 1) & 1) ^ 1);
      mbar_spin(bars + kBarFullQ, 0);
      if (elect_one()) {
        mbar_expect_tx(bars + kBarFullV, kTileBytes);
        bulk_load_mc(sbase + kSmemV + rank * (kTileBytes / 2), image(kSteps - 1, rank * (kTileBytes / 2)),
                     kTileBytes / 2, bars + kBarFullV);
        mbar_expect_tx(bars + kBarParams, kChunkBytes);
        load_p(1, 1, bars + kBarParams);
      }
      __syncwarp();
      unsigned done = 0;
      if (lane == 0)
        asm volatile("atom.global.add.u32 %0, [%1], 1;" : "=r"(done) : "l"(p.flags + kFlagDone) : "memory");
      if (__shfl_sync(0xffffffffu, done, 0) == kOwners - 1) {
#pragma unroll
        for (int j = 0; j < 8 * kFlagsPerGroup / 128; j++) ((uint4*)p.flags)[j * 32 + lane] = make_uint4(0, 0, 0, 0);
        if (lane <= 16) p.flags[kFlagHelper + lane] = 0;
      }
      __syncwarp();
      cluster_arrive();
#pragma unroll 1
      for (int j = 0; j < 6; j++) {
        const int w = j >= 3 ? 1 : 0;
        mbar_spin(bars + kBarTail + 8 * j, 0);
        asm volatile("fence.proxy.async.shared::cta;" ::: "memory");
        if (elect_one())
          tma_store_2d(&tmo, sbase + kSmemV + kTileBytes + j * 8192, (j - 3 * w) * 64,
                       ((kWaves - 1) * 8 + grp) * kS + mt * 128 + w * 64);
        __syncwarp();
      }
      if (elect_one()) asm volatile("cp.async.bulk.commit_group;\ncp.async.bulk.wait_group.read 0;" ::: "memory");

    } else {
      const uint32_t t = threadIdx.x - 288;
      auto throttle = [&](int i) {
#pragma unroll 1
        for (int n = 0; n < 100000; n++) {
          int prog;
          asm volatile("ld.volatile.shared.u32 %0, [%1];" : "=r"(prog) : "r"(bars + kProgress) : "memory");
          if (__all_sync(0xffffffffu, i <= prog + kLead)) break;
          __nanosleep(200);
        }
      };
      asm volatile("bar.sync 3, 192;" ::: "memory");
      publish(p, 1, grp);
      Unit v, k;
      load_unit<false>(p, unit_row(3, grp, mt), t, k);
      load_unit<true>(p, unit_row(2, grp, mt), t, v);
#pragma unroll 1
      for (int i = 2; i < kSteps; i++) {
        throttle(i - (i >= kOwn));
        if (i + 1 < kOwn) store_k(unit_dst<false>(p, i + 1, grp, mt, t), ((i + 1) >> 4) & 1, t, k, bars, codes_are_bytes(k));
        load_unit<false>(p, unit_row(min(i + 2, kOwn - 1), grp, mt), t, k);
        store_v_any(p, i, grp, mt, t, v, bars);
        if (i & 1) publish(p, i, grp);
        load_unit<true>(p, unit_row(min(i + 1, kSteps - 1), grp, mt), t, v);
      }
    }
  } else {
    asm volatile("setmaxnreg.inc.sync.aligned.u32 224;");
    const int wg = warp >> 2;
    float S[64], O[96];
    uint32_t P[32];
    float m0 = 0.f, m1 = 0.f, l0 = 0.f, l1 = 0.f, h0 = 0.f, h1 = 0.f;
    bool shifted = false;
    auto release = [&](uint32_t bar) {
      if (lane < 2) mbar_arrive_cluster(bar, lane);
    };
    auto stage_o = [&](uint32_t stage, float f0, float f1, int c_lo, int c_hi) {
      const uint32_t addr = stage + ((warp & 3) * 16 + (lane & 15)) * 128 + (((lane >> 4) ^ (lane & 7)) << 4);
#pragma unroll
      for (int j = 4 * c_lo; j < 4 * c_hi; j++) {
        float* o = O + 8 * j;
#pragma unroll
        for (int i = 0; i < 8; i++) o[i] = (i & 2) ? fmaf(o[i], f1, h1) : fmaf(o[i], f0, h0);
        asm volatile("stmatrix.sync.aligned.m8n8.x4.shared.b16 [%0], {%1, %2, %3, %4};" ::"r"(
                         (addr ^ ((j & 3) * 32)) + (j >> 2) * 8192),
                     "r"(pack_bf16(o[0], o[1])), "r"(pack_bf16(o[2], o[3])), "r"(pack_bf16(o[4], o[5])),
                     "r"(pack_bf16(o[6], o[7]))
                     : "memory");
      }
    };
    auto staged = [&]() {
      __syncwarp();
      if (lane == 0) mbar_arrive_local(bars + kBarStaged + 8 * wg);
    };
    float sc0 = 1.f, sc1 = 1.f;
    auto quad_sum = [&](float x) {
      x += __shfl_xor_sync(0xffffffffu, x, 1);
      return x + __shfl_xor_sync(0xffffffffu, x, 2);
    };
    auto finish_l = [&](int wave, float& i0, float& i1) {
      const uint4 vp = lds128(bars + kParV + wave * 32);
      const float a = quad_sum(l0), b = quad_sum(l1);
      i0 = __fdividef(__uint_as_float(vp.z), a);
      i1 = __fdividef(__uint_as_float(vp.z), b);
      h0 = (a - 2.f * quad_sum(h0)) * i0 * __uint_as_float(vp.y);
      h1 = (b - 2.f * quad_sum(h1)) * i1 * __uint_as_float(vp.y);
    };
    auto issue_qk = [&](int s, int slot0) {
      const uint32_t kb = desc_lo(sbase + kSmemK, 16);
      const uint32_t qb = desc_lo(sbase + kSmemQ, 16) + wg * 1536;
#pragma unroll
      for (int c = 0; c < 3; c++) {
        const int slot = slot0 + c >= 5 ? slot0 + c - 5 : slot0 + c;
        if (c == 2) {
          mbar_wait(bars + kBarFullK2, s & 1);
          if ((s & 15) == 0) mbar_wait(bars + kBarFullQ2 + 8 * wg, (s >> 4) & 1);
        }
#pragma unroll
        for (int kk = 0; kk < 4; kk++)
          wgmma_ss_n128(S, desc64<1024>(qb + c * 512 + kk * 2), desc64<1024>(kb + slot * 1024 + kk * 2),
                        c + kk > 0);
        if (c != 1) wg_commit();
      }
    };
    auto issue_pv = [&](int s) {
      const uint32_t vb = desc_lo(sbase + kSmemV, 1024) + (s & 1) * (kTileBytes >> 4);
      const int acc = (s & 15) != 0;
      auto run = [&](int lo, int hi, int acc0) {
#pragma unroll
        for (int kk = lo; kk < hi; kk++)
          wgmma_rs_n192t(O, P[kk * 4], P[kk * 4 + 1], P[kk * 4 + 2], P[kk * 4 + 3], desc64<3072>(vb + kk * 384),
                         kk > 0 ? 1 : acc0);
      };
      if (acc) {
        wg_fence();
        run(0, 8, 1);
        wg_commit();
      } else {
        wg_fence();
        run(0, 4, 0);
        mbar_wait(bars + kBarFullV2, (s >> 4) & 1);
        wg_fence();
        run(4, 8, 1);
        wg_commit();
      }
    };
    auto shift = [&](int lo, float d0, float d1) {
#pragma unroll
      for (int i = lo; i < 64; i += 4) {
        S[i] -= d0;
        S[i + 1] -= d0;
        S[i + 2] -= d1;
        S[i + 3] -= d1;
      }
    };
    auto unsafe = [&](int lo, int hi, bool first) {
      int a0 = 0, a1 = 0, b0 = 0, b1 = 0;
#pragma unroll
      for (int i = lo; i < hi; i += 8) {
        a0 = __vimax3_s32(a0, __float_as_int(S[i]), __float_as_int(S[i + 1]));
        a1 = __vimax3_s32(a1, __float_as_int(S[i + 2]), __float_as_int(S[i + 3]));
        b0 = __vimax3_s32(b0, __float_as_int(S[i + 4]), __float_as_int(S[i + 5]));
        b1 = __vimax3_s32(b1, __float_as_int(S[i + 6]), __float_as_int(S[i + 7]));
      }
      bool bad = __vimax3_s32(max(a0, b0), a1, b1) > __float_as_int(kLazyAbove);
      if (first) {
        uint32_t u0 = ~0u, u1 = ~0u;
#pragma unroll
        for (int i = 0; i < 16; i += 4) {
          u0 = __vimin3_u32(u0, __float_as_uint(S[i]), __float_as_uint(S[i + 1]));
          u1 = __vimin3_u32(u1, __float_as_uint(S[i + 2]), __float_as_uint(S[i + 3]));
        }
        bad |= max(u0, u1) >= __float_as_uint(-kLazyBelow);
      }
      return __any_sync(0xffffffffu, bad);
    };
    float e0, e1;
    auto use_true_max = [&](int lo, bool first, bool boundary, float& f0, float& f1) {
      float d0 = S[lo], d1 = S[lo + 2];
#pragma unroll
      for (int i = lo; i < 64; i += 4) {
        d0 = fmaxf(d0, fmaxf(S[i], S[i + 1]));
        d1 = fmaxf(d1, fmaxf(S[i + 2], S[i + 3]));
      }
      d0 = fmaxf(d0, __shfl_xor_sync(0xffffffffu, d0, 1));
      d1 = fmaxf(d1, __shfl_xor_sync(0xffffffffu, d1, 1));
      d0 = fmaxf(d0, __shfl_xor_sync(0xffffffffu, d0, 2));
      d1 = fmaxf(d1, __shfl_xor_sync(0xffffffffu, d1, 2));
      if (!first) {
        d0 = fmaxf(d0, 0.f);
        d1 = fmaxf(d1, 0.f);
        f0 = ex2(-d0);
        f1 = ex2(-d1);
        l0 *= f0;
        l1 *= f1;
        if (!boundary) {
          h0 *= f0;
          h1 *= f1;
        }
#pragma unroll
        for (int i = 0; i < lo; i++) S[i] *= (i & 2) ? f1 : f0;
      }
      if (lo > 0) shift(lo, d0, d1);
      e0 = d0;
      e1 = d1;
      m0 += d0;
      m1 += d1;
      shifted = true;
    };
    auto exps = [&](int lo, int hi) {
#pragma unroll
      for (int i = lo; i < hi; i += 4) {
        S[i] = ex2(S[i]);
        S[i + 1] = ex2(S[i + 1]);
        S[i + 2] = ex2(S[i + 2]);
        S[i + 3] = ex2(S[i + 3]);
        l0 += S[i] + S[i + 1];
        l1 += S[i + 2] + S[i + 3];
      }
    };
    auto to_p = [&]() {
#pragma unroll
      for (int j = 0; j < 32; j++) P[j] = pack_f16(S[2 * j], S[2 * j + 1]);
    };
    auto scale_o = [&](float f0, float f1) {
#pragma unroll
      for (int i = 0; i < 96; i += 4) {
        O[i] *= f0;
        O[i + 1] *= f0;
        O[i + 2] *= f1;
        O[i + 3] *= f1;
      }
    };
#pragma unroll
    for (int i = 0; i < 96; i++) asm volatile("" : "=f"(O[i]));
#pragma unroll
    for (int i = 0; i < 32; i++) asm volatile("" : "=r"(P[i]));
    if (threadIdx.x == 128) asm volatile("prefetch.tensormap [%0];" ::"l"(&tmo) : "memory");
    if (wg == 1) bar_arrive(1);
    int slot0 = 2;
#pragma unroll 1
    for (int s = 0; s < kOwn; s++) {
      const bool boundary = (s & 15) == 0;
      slot0 = slot0 >= 2 ? slot0 - 2 : slot0 + 3;
      if (boundary) mbar_wait(bars + kBarFullQ + 8 * wg, (s >> 4) & 1);
      mbar_wait(bars + kBarFullK01 + 8 * (s & 1), (s >> 1) & 1);
      bar_sync(1 + wg);
      pin(P);
      pin(O);
      wg_fence();
      issue_qk(s, slot0);
      mbar_wait(bars + kBarFullV + 8 * ((s - 1) & 1), ((s - 1) >> 1) & 1);
      wg_wait<1>();
      release(bars + kBarEmptyK0);
      if (s > 0) issue_pv(s - 1);
      else wg_commit();
      bar_arrive(2 - wg);
      wg_wait<1>();
      pin(S);
      release(bars + kBarEmptyK12 + 8 * (s & 1));
      if ((s & 15) == 15 && lane == 0) mbar_arrive_local(bars + kBarEmptyQ + 8 * wg);
      bool rescale = false;
      e0 = m0;
      e1 = m1;
#pragma unroll 1
      for (;;) {
        if (shifted) shift(0, e0, e1);
        if (rescale || !unsafe(0, kExpSplit, boundary)) break;
        use_true_max(0, boundary, boundary, sc0, sc1);
        rescale = true;
      }
      const bool late = unsafe(kExpSplit, 64, false);
      exps(0, kExpSplit);
      pin(S);
      asm volatile("st.volatile.shared.f32 [%0], %1;" ::"r"(bars + kDummy), "f"(l0 + l1) : "memory");
      wg_wait<0>();
      pin(O);
      pin(P);
      if (s > 0) {
        release(bars + kBarEmptyV + 8 * ((s - 1) & 1));
        if (((s + wg) & 15) == 0 && lane == 0) mbar_arrive_local(bars + kBarStage + 8 * (1 - wg));
      }
      if (late) {
        float f0, f1;
        use_true_max(kExpSplit, false, boundary, f0, f1);
        if (!boundary) {
          sc0 = f0;
          sc1 = f1;
          rescale = true;
        }
      }
      if (boundary && s > 0) {
        mbar_spin(bars + kBarStage + 8 * wg, ((s >> 4) - 1) & 1);
        pin(S);
        stage_o(sbase + kSmemV + wg * kTileBytes + kTileBytes / 2, sc0, sc1, 0, 3);
        staged();
        exps(kExpSplit, 64);
        to_p();
      } else {
        if (rescale && s > 0) scale_o(sc0, sc1);
        pin(S);
        exps(kExpSplit, 64);
        to_p();
        if ((s & 15) == 7) {
          h0 = l0;
          h1 = l1;
        }
        if ((s & 15) == 15) {
          finish_l(s >> 4, sc0, sc1);
          m0 = m1 = l0 = l1 = 0.f;
          shifted = false;
        }
      }
    }
    cluster_arrive();
    auto full_pv = [&](uint32_t v) {
      bar_sync(1 + wg);
      pin(P);
      pin(O);
      wg_fence();
      const uint32_t vb = desc_lo(sbase + v, 1024);
#pragma unroll
      for (int kk = 0; kk < 8; kk++)
        wgmma_rs_n192t(O, P[kk * 4], P[kk * 4 + 1], P[kk * 4 + 2], P[kk * 4 + 3], desc64<3072>(vb + kk * 384), 1);
      wg_commit();
    };
    mbar_spin(bars + kBarFullV + 8, ((kOwn - 1) >> 1) & 1);
    full_pv(kSmemV + kTileBytes);
    bar_arrive(2 - wg);
    mbar_spin(bars + kBarUnits, 1);
    const uint2 r = lds64(bars + kOffK + (threadIdx.x >> 2) * 8);
    float r0 = __uint_as_float(r.x), r1 = __uint_as_float(r.y);
    const uint32_t src = sbase + kSmemK + (threadIdx.x & 127) * 16;
    const uint32_t src0 = src + (wg ? slot_p(0, 1) : slot_p(0, 0)) * kChunkBytes;
    const uint32_t src1 = src + (wg ? slot_p(1, 1) : slot_p(1, 0)) * kChunkBytes;
    const bool rescale = shifted || __any_sync(0xffffffffu, r0 < 0.f);
    float f0, f1;
    if (rescale) {
      mbar_spin(bars + (wg ? kBarParams : kBarCodes), 1);
      float4 b = make_float4(0.f, 0.f, 0.f, 0.f), c = make_float4(r0, r1, 0.f, 0.f);
      if (r0 < 0.f) {
        const float4* extra = (const float4*)(p.prob + (size_t)(blockIdx.x * kProbBytes + kProbExtra + (threadIdx.x >> 2) * 32));
        b = __ldcg(extra);
        c = __ldcg(extra + 1);
      }
      const float n0 = fmaxf(m0, fmaxf(b.x, b.z)), n1 = fmaxf(m1, fmaxf(b.y, b.w));
      f0 = ex2(m0 - n0);
      f1 = ex2(m1 - n1);
      b = make_float4(ex2(b.x - n0), ex2(b.y - n1), ex2(b.z - n0), ex2(b.w - n1));
      l0 *= f0;
      l1 *= f1;
      h0 *= f0;
      h1 *= f1;
      r0 = c.x * b.x + c.z * b.z;
      r1 = c.y * b.y + c.w * b.w;
#pragma unroll 1
      for (int i = 0; i < 32; i++) {
        const uint32_t a = (i < 16 ? src0 : src1) + (i & 14) * 1024 + (i & 1) * 8;
        const uint2 x = lds64(a);
        put64(a, scale_f16(x.x, i < 16 ? b.x : b.z), scale_f16(x.y, i < 16 ? b.y : b.w));
      }
    }
    auto take = [&](uint32_t (&A)[32], uint32_t a) {
#pragma unroll
      for (int i = 0; i < 8; i++) {
        const uint4 x = lds128v(a + i * 2048);
        A[4 * i] = x.x, A[4 * i + 1] = x.y, A[4 * i + 2] = x.z, A[4 * i + 3] = x.w;
      }
      pin(A);
    };
    uint32_t R[32];
    l0 += r0;
    l1 += r1;
    finish_l(kWaves - 1, sc0, sc1);
    asm volatile("st.volatile.shared.f32 [%0], %1;" ::"r"(bars + kDummy), "f"(h0 + h1) : "memory");
    wg_wait<0>();
    pin(O);
    pin(P);
    if (rescale) scale_o(f0, f1);
    take(P, src0);
    mbar_spin(bars + kBarFullQ, 0);
    full_pv(kSmemQ);
    mbar_spin(bars + (wg ? kBarParams : kBarCodes), 1);
    take(R, src1);
    float T0[32], T1[32];
    auto tail_pv = [&](float (&T)[32], int c) {
      const uint32_t vb = desc_lo(sbase + kSmemV, 1024) + c * 64;
      wg_fence();
#pragma unroll
      for (int kk = 0; kk < 8; kk++)
        wgmma_rs_n64t(T, R[kk * 4], R[kk * 4 + 1], R[kk * 4 + 2], R[kk * 4 + 3], desc64<3072>(vb + kk * 384), kk > 0);
      wg_commit();
    };
    uint32_t X[16];
    auto tail_pack = [&](float (&T)[32], int c) {
      pin(T);
#pragma unroll
      for (int i = 0; i < 16; i++) {
        const float f = (i & 1) ? sc1 : sc0;
        X[i] = pack_bf16(fmaf(T[2 * i], f, O[32 * c + 2 * i]), fmaf(T[2 * i + 1], f, O[32 * c + 2 * i + 1]));
      }
      pin(X);
    };
    auto tail_store = [&](int c) {
      const uint32_t addr = sbase + kSmemV + kTileBytes + wg * (kTileBytes / 2) + c * 8192 +
                            ((warp & 3) * 16 + (lane & 15)) * 128 + (((lane >> 4) ^ (lane & 7)) << 4);
#pragma unroll
      for (int j = 0; j < 4; j++)
        asm volatile("stmatrix.sync.aligned.m8n8.x4.shared.b16 [%0], {%1, %2, %3, %4};" ::"r"(addr ^ (j * 32)), "r"(X[4 * j]),
                     "r"(X[4 * j + 1]), "r"(X[4 * j + 2]), "r"(X[4 * j + 3])
                     : "memory");
      __syncwarp();
      if (lane == 0) mbar_arrive_local(bars + kBarTail + 24 * wg + 8 * c);
    };
    mbar_spin(bars + kBarFullV, (kOwn >> 1) & 1);
    tail_pv(T0, 0);
    wg_wait<1>();
    pin(P);
    auto prescale = [&](int c) {
      pin(O);
#pragma unroll
      for (int i = 32 * c; i < 32 * c + 32; i++) O[i] = (i & 2) ? fmaf(O[i], sc1, h1) : fmaf(O[i], sc0, h0);
      pin(O);
      mbar_spin(bars + kBarFullV, (kOwn >> 1) & 1);
    };
    prescale(0);
    tail_pv(T1, 1);
    if (wg == 0) bar_arrive(2);
    wg_wait<1>();
    tail_pack(T0, 0);
    tail_store(0);
    tail_pv(T0, 2);
    prescale(1);
    wg_wait<1>();
    tail_pack(T1, 1);
    tail_store(1);
    prescale(2);
    wg_wait<0>();
    tail_pack(T0, 2);
    tail_store(2);
    cluster_wait();
  }
}

}

extern "C" void kernel_launch(void* const* d_in, const int* in_sizes, int n_in, void* d_out, int out_size) {
  static CUtensorMap tmq, tmo;
  static const void *tm_q = nullptr, *tm_o = nullptr;
  static void *scratch, *flags, *prob;
  if (tm_q != d_in[0] || tm_o != d_out) {
    typedef CUresult (*EncodeFn)(CUtensorMap*, CUtensorMapDataType, cuuint32_t, void*, const cuuint64_t*,
                                 const cuuint64_t*, const cuuint32_t*, const cuuint32_t*, CUtensorMapInterleave,
                                 CUtensorMapSwizzle, CUtensorMapL2promotion, CUtensorMapFloatOOBfill);
    void* fn = nullptr;
    cudaDriverEntryPointQueryResult qr;
    cudaGetDriverEntryPoint("cuTensorMapEncodeTiled", &fn, cudaEnableDefault, &qr);
    cuuint64_t dims[2] = {(cuuint64_t)kD, (cuuint64_t)kH * kS};
    cuuint64_t strides[1] = {(cuuint64_t)kD * 2};
    cuuint32_t box[2] = {64, 64};
    cuuint32_t estr[2] = {1, 1};
    ((EncodeFn)fn)(&tmq, CU_TENSOR_MAP_DATA_TYPE_BFLOAT16, 2, d_in[0], dims, strides, box, estr,
                   CU_TENSOR_MAP_INTERLEAVE_NONE, CU_TENSOR_MAP_SWIZZLE_128B, CU_TENSOR_MAP_L2_PROMOTION_L2_128B,
                   CU_TENSOR_MAP_FLOAT_OOB_FILL_NONE);
    ((EncodeFn)fn)(&tmo, CU_TENSOR_MAP_DATA_TYPE_BFLOAT16, 2, d_out, dims, strides, box, estr,
                   CU_TENSOR_MAP_INTERLEAVE_NONE, CU_TENSOR_MAP_SWIZZLE_128B, CU_TENSOR_MAP_L2_PROMOTION_NONE,
                   CU_TENSOR_MAP_FLOAT_OOB_FILL_NONE);
    cudaFuncSetAttribute(attn_kernel, cudaFuncAttributeMaxDynamicSharedMemorySize, kSmemTotal);
    cudaGetSymbolAddress(&scratch, g_scratch);
    cudaGetSymbolAddress(&flags, g_flags);
    cudaGetSymbolAddress(&prob, g_prob);
    tm_q = d_in[0];
    tm_o = d_out;
  }
  Params p;
  p.q = (const __nv_bfloat16*)d_in[0];
  p.qk = (const int*)d_in[1];
  p.qv = (const int*)d_in[2];
  p.ks = (const __nv_bfloat16*)d_in[3];
  p.kz = (const __nv_bfloat16*)d_in[4];
  p.vs = (const __nv_bfloat16*)d_in[5];
  p.vz = (const __nv_bfloat16*)d_in[6];
  p.scratch = (uint8_t*)scratch;
  p.flags = (unsigned*)flags;
  p.prob = (uint8_t*)prob;
  attn_kernel<<<kOwners + kHelpers, 384, kSmemTotal>>>(p, tmq, tmo);
}
```

```cpp
#include <cuda_runtime.h>
#include <cuda_bf16.h>
#include <cuda.h>
#include <math.h>
#include <stdint.h>

namespace {

constexpr int kH = 32, kS = 2048, kD = 192;
constexpr int kGroupTok = 64;
constexpr int kBN = 128;
constexpr int kNBlk = kS / kBN;
constexpr int kWaves = 4;
constexpr int kSteps = kWaves * kNBlk;
constexpr int kTileBytes = kBN * kD * 2;
constexpr int kOwners = 128, kHelpers = 4;
constexpr uint32_t kTails = 0x33222112u;
constexpr uint32_t kJobs = 0x30214567u;
constexpr int kMaxTail = 3;
__device__ __forceinline__ int tail_blocks(int grp) { return (kTails >> (4 * grp)) & 3; }
constexpr uint32_t kHelperDelay = 42000, kHelperPrepare = 12000;
constexpr int kProbExtra = 512, kProbData = 4096, kProbBytes = kProbData + 2 * kMaxTail * 16384;
constexpr int kFlagTarget = 48;
constexpr int kFlagsPerGroup = kSteps;
constexpr float kLazyAbove = 15.f, kLazyBelow = 7.f;
constexpr int kLead = 3;
constexpr int kRing = 2 * kLead + 2;
static_assert((kRing & (kRing - 1)) == 0, "power of two");
constexpr int kBarPolls = 1 << 13, kFlagPolls = 1 << 16;

constexpr uint64_t pack_delays(int a, int b, int c, int d, int e, int f, int g, int h) {
  const int t[8] = {a, b, c, d, e, f, g, h};
  uint64_t w = 0;
  for (int i = 0; i < 8; i++) w |= (uint64_t)((t[i] + 16) / 32) << 8 * i;
  return w;
}
constexpr uint64_t kCodeDelays = pack_delays(500, 0, 0, 750, 1000, 1250, 1500, 1750), kQueryDelays = pack_delays(3340, 1900, 2600, 3860, 4380, 4900, 5420, 5940);
constexpr int kStatStep = 9;
static_assert(kStatStep + kLead < 15, "the first block of a head is expanded after its statistics have arrived");
constexpr uint32_t kOffsetFactor = 0x3E553E55u;
constexpr int kExpSplit = 32;
constexpr int kChunkBytes = kBN * 128;
constexpr int kSmemQ = 0;
constexpr int kSmemK = kTileBytes;
constexpr int kSmemV = kSmemK + 5 * kChunkBytes;
constexpr int kSmemBar = kSmemV + 2 * kTileBytes;
constexpr int kOffK = 256, kParV = kOffK + 2 * kD * 2, kBarBytes = kParV + 128;
constexpr int kSmemTotal = kSmemBar + kBarBytes + 1024;

constexpr int kBarFullK01 = 0, kBarFullV = 16, kBarEmptyK12 = 32, kBarEmptyV = 48, kBarFullQ = 64, kBarEmptyQ = 80,
              kBarFullK2 = 96, kBarEmptyK0 = 104, kBarStage = 112, kBarStaged = 128, kBarFullV2 = 144,
              kBarFullQ2 = 152, kBarCodes = 168, kBarTail = 176, kProgress = 224, kDummy = 228, kBarParams = 232,
              kBarUnits = 240;

constexpr uint32_t v_places(int n) {
  uint32_t w = (kSmemQ >> 14 | kBarFullQ << 1) << 8;
  for (int x = 0; x <= n; x += x ? 1 : 2) {
    const int v = kSteps - n + x - (x ? 2 : 1);
    w |= ((kSmemV + (v & 1) * kTileBytes) >> 14 | (v & 2) << 1 | (kBarFullV + 8 * (v & 1)) << 1) << 8 * x;
  }
  return w;
}
constexpr uint32_t p_places(int n, int wg) {
  constexpr int bar[6] = {kBarUnits, kBarUnits, kBarCodes, kBarParams, kBarFullQ + 8, kBarFullQ2};
  uint32_t w = 0;
  for (int j = 0; j < n; j++)
    w |= ((kSmemK >> 14) + (3 * (kSteps - n) + 2 * j + wg) % 5 | (j < 2) << 3 | bar[2 * j + wg] << 1) << 10 * j;
  return w;
}
template <int n> constexpr uint32_t kPlacesV = v_places(n);
template <int n, int wg> constexpr uint32_t kPlacesP = p_places(n, wg);
__device__ __forceinline__ uint32_t pick(int n, uint32_t a, uint32_t b, uint32_t c) { return n == 1 ? a : n == 2 ? b : c; }

__device__ __align__(1024) uint4 g_scratch[(size_t)8 * kRing * 2 * kTileBytes / 16];
constexpr int kFlagHelper = 8 * kFlagsPerGroup, kFlagStats = kFlagHelper + 8, kFlagDone = kFlagStats + 8;
__device__ __align__(16) unsigned g_flags[kFlagDone + 1];
constexpr int kHelperImages = kOwners * kProbBytes, kHeadStats = kHelperImages + 8 * kMaxTail * kTileBytes;
__device__ __align__(1024) uint4 g_prob[(kHeadStats + kH * 512) / 16];

__device__ __forceinline__ void wgmma_ss_n128(float (&d)[64], uint64_t da, uint64_t db, int scale_d) {
  asm volatile("{\n.reg .pred p;\nsetp.ne.b32 p, %66, 0;\n"
    "wgmma.mma_async.sync.aligned.m64n128k16.f32.bf16.bf16 "
    "{%0, %1, %2, %3, %4, %5, %6, %7, %8, %9, %10, %11, %12, %13, %14, %15, %16, %17, %18, %19, %20, %21, %22, %23, %24, %25, %26, %27, %28, %29, %30, %31, %32, %33, %34, %35, %36, %37, %38, %39, %40, %41, %42, %43, %44, %45, %46, %47, %48, %49, %50, %51, %52, %53, %54, %55, %56, %57, %58, %59, %60, %61, %62, %63}, %64, %65, p, 1, 1, 0, 0;\n}\n"
    : "+f"(d[0]), "+f"(d[1]), "+f"(d[2]), "+f"(d[3]), "+f"(d[4]), "+f"(d[5]), "+f"(d[6]), "+f"(d[7]), "+f"(d[8]), "+f"(d[9]), "+f"(d[10]), "+f"(d[11]), "+f"(d[12]), "+f"(d[13]), "+f"(d[14]), "+f"(d[15]), "+f"(d[16]), "+f"(d[17]), "+f"(d[18]), "+f"(d[19]), "+f"(d[20]), "+f"(d[21]), "+f"(d[22]), "+f"(d[23]), "+f"(d[24]), "+f"(d[25]), "+f"(d[26]), "+f"(d[27]), "+f"(d[28]), "+f"(d[29]), "+f"(d[30]), "+f"(d[31]), "+f"(d[32]), "+f"(d[33]), "+f"(d[34]), "+f"(d[35]), "+f"(d[36]), "+f"(d[37]), "+f"(d[38]), "+f"(d[39]), "+f"(d[40]), "+f"(d[41]), "+f"(d[42]), "+f"(d[43]), "+f"(d[44]), "+f"(d[45]), "+f"(d[46]), "+f"(d[47]), "+f"(d[48]), "+f"(d[49]), "+f"(d[50]), "+f"(d[51]), "+f"(d[52]), "+f"(d[53]), "+f"(d[54]), "+f"(d[55]), "+f"(d[56]), "+f"(d[57]), "+f"(d[58]), "+f"(d[59]), "+f"(d[60]), "+f"(d[61]), "+f"(d[62]), "+f"(d[63])
    : "l"(da), "l"(db), "r"(scale_d));
}
__device__ __forceinline__ void wgmma_new_n128(float (&d)[64], uint64_t da, uint64_t db) {
  asm volatile("{\n.reg .pred p;\nsetp.ne.b32 p, 0, 0;\n"
    "wgmma.mma_async.sync.aligned.m64n128k16.f32.bf16.bf16 "
    "{%0, %1, %2, %3, %4, %5, %6, %7, %8, %9, %10, %11, %12, %13, %14, %15, %16, %17, %18, %19, %20, %21, %22, %23, %24, %25, %26, %27, %28, %29, %30, %31, %32, %33, %34, %35, %36, %37, %38, %39, %40, %41, %42, %43, %44, %45, %46, %47, %48, %49, %50, %51, %52, %53, %54, %55, %56, %57, %58, %59, %60, %61, %62, %63}, %64, %65, p, 1, 1, 0, 0;\n}\n"
    : "=f"(d[0]), "=f"(d[1]), "=f"(d[2]), "=f"(d[3]), "=f"(d[4]), "=f"(d[5]), "=f"(d[6]), "=f"(d[7]), "=f"(d[8]), "=f"(d[9]), "=f"(d[10]), "=f"(d[11]), "=f"(d[12]), "=f"(d[13]), "=f"(d[14]), "=f"(d[15]), "=f"(d[16]), "=f"(d[17]), "=f"(d[18]), "=f"(d[19]), "=f"(d[20]), "=f"(d[21]), "=f"(d[22]), "=f"(d[23]), "=f"(d[24]), "=f"(d[25]), "=f"(d[26]), "=f"(d[27]), "=f"(d[28]), "=f"(d[29]), "=f"(d[30]), "=f"(d[31]), "=f"(d[32]), "=f"(d[33]), "=f"(d[34]), "=f"(d[35]), "=f"(d[36]), "=f"(d[37]), "=f"(d[38]), "=f"(d[39]), "=f"(d[40]), "=f"(d[41]), "=f"(d[42]), "=f"(d[43]), "=f"(d[44]), "=f"(d[45]), "=f"(d[46]), "=f"(d[47]), "=f"(d[48]), "=f"(d[49]), "=f"(d[50]), "=f"(d[51]), "=f"(d[52]), "=f"(d[53]), "=f"(d[54]), "=f"(d[55]), "=f"(d[56]), "=f"(d[57]), "=f"(d[58]), "=f"(d[59]), "=f"(d[60]), "=f"(d[61]), "=f"(d[62]), "=f"(d[63])
    : "l"(da), "l"(db));
}
__device__ __forceinline__ void wgmma_rs_n64t(float (&d)[32], uint32_t a0, uint32_t a1, uint32_t a2, uint32_t a3, uint64_t db, int scale_d) {
  asm volatile("{\n.reg .pred p;\nsetp.ne.b32 p, %37, 0;\n"
    "wgmma.mma_async.sync.aligned.m64n64k16.f32.f16.f16 "
    "{%0, %1, %2, %3, %4, %5, %6, %7, %8, %9, %10, %11, %12, %13, %14, %15, %16, %17, %18, %19, %20, %21, %22, %23, %24, %25, %26, %27, %28, %29, %30, %31}, {%32, %33, %34, %35}, %36, p, 1, 1, 1;\n}\n"
    : "+f"(d[0]), "+f"(d[1]), "+f"(d[2]), "+f"(d[3]), "+f"(d[4]), "+f"(d[5]), "+f"(d[6]), "+f"(d[7]), "+f"(d[8]), "+f"(d[9]), "+f"(d[10]), "+f"(d[11]), "+f"(d[12]), "+f"(d[13]), "+f"(d[14]), "+f"(d[15]), "+f"(d[16]), "+f"(d[17]), "+f"(d[18]), "+f"(d[19]), "+f"(d[20]), "+f"(d[21]), "+f"(d[22]), "+f"(d[23]), "+f"(d[24]), "+f"(d[25]), "+f"(d[26]), "+f"(d[27]), "+f"(d[28]), "+f"(d[29]), "+f"(d[30]), "+f"(d[31])
    : "r"(a0), "r"(a1), "r"(a2), "r"(a3), "l"(db), "r"(scale_d));
}
__device__ __forceinline__ void wgmma_rs_n192t(float (&d)[96], uint32_t a0, uint32_t a1, uint32_t a2, uint32_t a3, uint64_t db, int scale_d) {
  asm volatile("{\n.reg .pred p;\nsetp.ne.b32 p, %101, 0;\n"
    "wgmma.mma_async.sync.aligned.m64n192k16.f32.f16.f16 "
    "{%0, %1, %2, %3, %4, %5, %6, %7, %8, %9, %10, %11, %12, %13, %14, %15, %16, %17, %18, %19, %20, %21, %22, %23, %24, %25, %26, %27, %28, %29, %30, %31, %32, %33, %34, %35, %36, %37, %38, %39, %40, %41, %42, %43, %44, %45, %46, %47, %48, %49, %50, %51, %52, %53, %54, %55, %56, %57, %58, %59, %60, %61, %62, %63, %64, %65, %66, %67, %68, %69, %70, %71, %72, %73, %74, %75, %76, %77, %78, %79, %80, %81, %82, %83, %84, %85, %86, %87, %88, %89, %90, %91, %92, %93, %94, %95}, {%96, %97, %98, %99}, %100, p, 1, 1, 1;\n}\n"
    : "+f"(d[0]), "+f"(d[1]), "+f"(d[2]), "+f"(d[3]), "+f"(d[4]), "+f"(d[5]), "+f"(d[6]), "+f"(d[7]), "+f"(d[8]), "+f"(d[9]), "+f"(d[10]), "+f"(d[11]), "+f"(d[12]), "+f"(d[13]), "+f"(d[14]), "+f"(d[15]), "+f"(d[16]), "+f"(d[17]), "+f"(d[18]), "+f"(d[19]), "+f"(d[20]), "+f"(d[21]), "+f"(d[22]), "+f"(d[23]), "+f"(d[24]), "+f"(d[25]), "+f"(d[26]), "+f"(d[27]), "+f"(d[28]), "+f"(d[29]), "+f"(d[30]), "+f"(d[31]), "+f"(d[32]), "+f"(d[33]), "+f"(d[34]), "+f"(d[35]), "+f"(d[36]), "+f"(d[37]), "+f"(d[38]), "+f"(d[39]), "+f"(d[40]), "+f"(d[41]), "+f"(d[42]), "+f"(d[43]), "+f"(d[44]), "+f"(d[45]), "+f"(d[46]), "+f"(d[47]), "+f"(d[48]), "+f"(d[49]), "+f"(d[50]), "+f"(d[51]), "+f"(d[52]), "+f"(d[53]), "+f"(d[54]), "+f"(d[55]), "+f"(d[56]), "+f"(d[57]), "+f"(d[58]), "+f"(d[59]), "+f"(d[60]), "+f"(d[61]), "+f"(d[62]), "+f"(d[63]), "+f"(d[64]), "+f"(d[65]), "+f"(d[66]), "+f"(d[67]), "+f"(d[68]), "+f"(d[69]), "+f"(d[70]), "+f"(d[71]), "+f"(d[72]), "+f"(d[73]), "+f"(d[74]), "+f"(d[75]), "+f"(d[76]), "+f"(d[77]), "+f"(d[78]), "+f"(d[79]), "+f"(d[80]), "+f"(d[81]), "+f"(d[82]), "+f"(d[83]), "+f"(d[84]), "+f"(d[85]), "+f"(d[86]), "+f"(d[87]), "+f"(d[88]), "+f"(d[89]), "+f"(d[90]), "+f"(d[91]), "+f"(d[92]), "+f"(d[93]), "+f"(d[94]), "+f"(d[95])
    : "r"(a0), "r"(a1), "r"(a2), "r"(a3), "l"(db), "r"(scale_d));
}

__device__ __forceinline__ uint32_t desc_lo(uint32_t addr, uint32_t lbo) { return ((addr & 0x3FFFF) >> 4) | ((lbo >> 4) << 16); }
template <uint32_t SBO>
__device__ __forceinline__ uint64_t desc64(uint32_t lo) {
  uint64_t d;
  asm("mov.b64 %0, {%1, %2};" : "=l"(d) : "r"(lo), "n"((SBO >> 4) | (1u << 30)));
  return d;
}
__device__ __forceinline__ void wg_fence() { asm volatile("wgmma.fence.sync.aligned;" ::: "memory"); }
__device__ __forceinline__ void wg_commit() { asm volatile("wgmma.commit_group.sync.aligned;" ::: "memory"); }
template <int N>
__device__ __forceinline__ void wg_wait() { asm volatile("wgmma.wait_group.sync.aligned %0;" ::"n"(N) : "memory"); }
__device__ __forceinline__ void bar_sync(int id) { asm volatile("bar.sync %0, 256;" ::"r"(id) : "memory"); }
__device__ __forceinline__ void bar_arrive(int id) { asm volatile("bar.arrive %0, 256;" ::"r"(id) : "memory"); }

template <int N>
__device__ __forceinline__ void pin(float (&r)[N]) {
#pragma unroll
  for (int i = 0; i < N; i++) asm volatile("" : "+f"(r[i])::"memory");
}
template <int N>
__device__ __forceinline__ void pin(uint32_t (&r)[N]) {
#pragma unroll
  for (int i = 0; i < N; i++) asm volatile("" : "+r"(r[i])::"memory");
}

__device__ __forceinline__ void mbar_init(uint32_t bar, uint32_t count) {
  asm volatile("mbarrier.init.shared::cta.b64 [%0], %1;" ::"r"(bar), "r"(count) : "memory");
}
__device__ __forceinline__ void mbar_expect_tx(uint32_t bar, uint32_t bytes) {
  asm volatile("mbarrier.arrive.expect_tx.shared::cta.b64 _, [%0], %1;" ::"r"(bar), "r"(bytes) : "memory");
}
__device__ __forceinline__ void mbar_arrive_local(uint32_t bar) {
  asm volatile("mbarrier.arrive.shared::cta.b64 _, [%0];" ::"r"(bar) : "memory");
}
__device__ __forceinline__ void mbar_arrive_cluster(uint32_t bar, uint32_t cta) {
  asm volatile(
      "{\n.reg .b32 ra;\nmapa.shared::cluster.u32 ra, %0, %1;\n"
      "mbarrier.arrive.shared::cluster.b64 _, [ra];\n}" ::"r"(bar),
      "r"(cta)
      : "memory");
}
__device__ __forceinline__ bool mbar_try(uint32_t bar, uint32_t parity) {
  uint32_t ok;
  asm volatile(
      "{\n.reg .pred p;\nmbarrier.try_wait.parity.shared::cta.b64 p, [%1], %2;\nselp.u32 %0, 1, 0, p;\n}"
      : "=r"(ok)
      : "r"(bar), "r"(parity)
      : "memory");
  return ok;
}
__device__ __forceinline__ uint32_t now_clk() {
  uint32_t t;
  asm volatile("mov.u32 %0, %%clock;" : "=r"(t));
  return t;
}
__device__ __forceinline__ void mbar_wait(uint32_t bar, uint32_t parity) {
  if (mbar_try(bar, parity)) return;
#pragma unroll 1
  for (int n = now_clk() & 1; n < kBarPolls; n++)
    if (mbar_try(bar, parity)) break;
}
__device__ __forceinline__ void mbar_spin(uint32_t bar, uint32_t parity) {
#pragma unroll 1
  for (int n = 0; n < kBarPolls; n++)
    if (mbar_try(bar, parity)) break;
}
__device__ __forceinline__ bool elect_one() {
  uint32_t r;
  asm volatile("{\n.reg .pred p;\nelect.sync _|p, 0xffffffff;\nselp.u32 %0, 1, 0, p;\n}" : "=r"(r));
  return r;
}
__device__ __forceinline__ void bulk_load(uint32_t dst, const void* src, uint32_t bytes, uint32_t bar) {
  asm volatile("cp.async.bulk.shared::cluster.global.mbarrier::complete_tx::bytes [%0], [%1], %2, [%3];" ::"r"(dst),
               "l"(src), "r"(bytes), "r"(bar)
               : "memory");
}
__device__ __forceinline__ void bulk_copy_peer(uint32_t addr, uint32_t bytes, uint32_t bar, uint32_t cta) {
  asm volatile(
      "{\n.reg .b32 ra, rb;\nmapa.shared::cluster.u32 ra, %0, %3;\nmapa.shared::cluster.u32 rb, %2, %3;\n"
      "cp.async.bulk.shared::cluster.shared::cta.mbarrier::complete_tx::bytes [ra], [%0], %1, [rb];\n}" ::"r"(addr),
      "r"(bytes), "r"(bar), "r"(cta)
      : "memory");
}
__device__ __forceinline__ void bulk_load_mc(uint32_t dst, const void* src, uint32_t bytes, uint32_t bar) {
  asm volatile(
      "cp.async.bulk.shared::cluster.global.mbarrier::complete_tx::bytes.multicast::cluster [%0], [%1], %2, [%3], "
      "%4;" ::"r"(dst),
      "l"(src), "r"(bytes), "r"(bar), "h"((uint16_t)3)
      : "memory");
}
constexpr uint64_t kEvictFirst = 0x12F0000000000000ull;
__device__ __forceinline__ void tma_load_2d(uint32_t dst, const CUtensorMap* map, int c0, int c1, uint32_t bar) {
  asm volatile(
      "cp.async.bulk.tensor.2d.shared::cluster.global.mbarrier::complete_tx::bytes.L2::cache_hint [%0], [%1, {%3, %4}], "
      "[%2], %5;" ::"r"(dst),
      "l"(map), "r"(bar), "r"(c0), "r"(c1), "l"(kEvictFirst)
      : "memory");
}
__device__ __forceinline__ void tma_store_2d(const CUtensorMap* map, uint32_t src, int c0, int c1) {
  asm volatile("cp.async.bulk.tensor.2d.global.shared::cta.bulk_group [%0, {%2, %3}], [%1];" ::"l"(map), "r"(src),
               "r"(c0), "r"(c1)
               : "memory");
}
__device__ __forceinline__ void cluster_arrive() { asm volatile("barrier.cluster.arrive.relaxed;" ::: "memory"); }
__device__ __forceinline__ void cluster_wait() { asm volatile("barrier.cluster.wait;" ::: "memory"); }
__device__ __forceinline__ float ex2(float x) {
  float y;
  asm("ex2.approx.ftz.f32 %0, %1;" : "=f"(y) : "f"(x));
  return y;
}
__device__ __forceinline__ float rcp(float x) {
  float y;
  asm("rcp.approx.ftz.f32 %0, %1;" : "=f"(y) : "f"(x));
  return y;
}
__device__ __forceinline__ uint32_t pack_bf16(float lo, float hi) {
  uint32_t r;
  asm("cvt.rn.bf16x2.f32 %0, %1, %2;" : "=r"(r) : "f"(hi), "f"(lo));
  return r;
}

__device__ __forceinline__ uint32_t pack_f16(float lo, float hi) {
  uint32_t r;
  asm("cvt.rn.f16x2.f32 %0, %1, %2;" : "=r"(r) : "f"(hi), "f"(lo));
  return r;
}

__device__ __forceinline__ uint32_t scale_f16(uint32_t w, float f) {
  float x, y;
  asm("{\n.reg .b16 a, b;\nmov.b32 {a, b}, %2;\ncvt.f32.f16 %0, a;\ncvt.f32.f16 %1, b;\n}" : "=f"(x), "=f"(y) : "r"(w));
  return pack_f16(x * f, y * f);
}

struct Params {
  const int* qk;
  const int* qv;
  const __nv_bfloat16* ks;
  const __nv_bfloat16* kz;
  const __nv_bfloat16* vs;
  const __nv_bfloat16* vz;
  const __nv_bfloat16* q;
  uint8_t* scratch;
  unsigned* flags;
  uint8_t* prob;
};

__device__ __forceinline__ int unit_row(int step, int grp, int mt) {
  return ((step >> 4) * 8 + grp) * kS + (step & 15) * kBN + mt * 8;
}
__device__ __forceinline__ uint8_t* tile_image(const Params& p, int step, int grp, int is_v) {
  return p.scratch + ((size_t)(grp * kRing + (unsigned)step % kRing) * 2 + is_v) * kTileBytes;
}
struct Unit { uint4 x[4]; uint2 s, z; };

__device__ __forceinline__ uint4 ldg128(const void* a) {
  uint4 v;
  asm volatile("ld.global.nc.L1::no_allocate.v4.u32 {%0, %1, %2, %3}, [%4];"
               : "=r"(v.x), "=r"(v.y), "=r"(v.z), "=r"(v.w)
               : "l"(a)
               : "memory");
  return v;
}
__device__ __forceinline__ uint4 ldg128_last_use(const void* a) {
  uint4 v;
  asm volatile("ld.global.nc.L1::no_allocate.L2::cache_hint.v4.u32 {%0, %1, %2, %3}, [%4], %5;"
               : "=r"(v.x), "=r"(v.y), "=r"(v.z), "=r"(v.w)
               : "l"(a), "l"(kEvictFirst)
               : "memory");
  return v;
}
__device__ __forceinline__ uint2 ldg64(const void* a) {
  uint2 v;
  asm volatile("ld.global.nc.L1::no_allocate.v2.u32 {%0, %1}, [%2];" : "=r"(v.x), "=r"(v.y) : "l"(a));
  return v;
}
__device__ __forceinline__ void stg64(uint64_t a, uint32_t x, uint32_t y) {
  asm volatile("st.global.L1::no_allocate.v2.u32 [%0], {%1, %2};" ::"l"(a), "r"(x), "r"(y) : "memory");
}
__device__ __forceinline__ uint32_t bf2_mul(uint32_t a, uint32_t b) {
  uint32_t r;
  asm("mul.rn.bf16x2 %0, %1, %2;" : "=r"(r) : "r"(a), "r"(b));
  return r;
}
__device__ __forceinline__ uint32_t bf2_fma(uint32_t a, uint32_t b, uint32_t c) {
  uint32_t r;
  asm("fma.rn.bf16x2 %0, %1, %2, %3;" : "=r"(r) : "r"(a), "r"(b), "r"(c));
  return r;
}
__device__ __forceinline__ uint32_t h2_fma(uint32_t a, uint32_t b, uint32_t c) {
  uint32_t r;
  asm("fma.rn.f16x2 %0, %1, %2, %3;" : "=r"(r) : "r"(a), "r"(b), "r"(c));
  return r;
}
__device__ __forceinline__ uint32_t h2_mul(uint32_t a, uint32_t b) {
  uint32_t r;
  asm("mul.rn.f16x2 %0, %1, %2;" : "=r"(r) : "r"(a), "r"(b));
  return r;
}
__device__ __forceinline__ float bf_lo(uint32_t w) { return __uint_as_float(w << 16); }
__device__ __forceinline__ float bf_hi(uint32_t w) { return __uint_as_float(w & 0xffff0000u); }
__device__ __forceinline__ uint32_t codes_bf16(uint32_t a, uint32_t b) { return pack_bf16((float)(int)a, (float)(int)b); }
__device__ __forceinline__ uint2 lds64(uint32_t a) {
  uint2 v;
  asm volatile("ld.shared.v2.u32 {%0, %1}, [%2];" : "=r"(v.x), "=r"(v.y) : "r"(a));
  return v;
}
__device__ __forceinline__ uint4 lds128(uint32_t a) {
  uint4 v;
  asm volatile("ld.shared.v4.u32 {%0, %1, %2, %3}, [%4];" : "=r"(v.x), "=r"(v.y), "=r"(v.z), "=r"(v.w) : "r"(a));
  return v;
}
__device__ __forceinline__ uint4 lds128v(uint32_t a) {
  uint4 v;
  asm volatile("ld.shared.v4.u32 {%0, %1, %2, %3}, [%4];" : "=r"(v.x), "=r"(v.y), "=r"(v.z), "=r"(v.w) : "r"(a) : "memory");
  return v;
}
__device__ __forceinline__ void scale_p(uint32_t a, float f0, float f1) {
#pragma unroll 1
  for (int i = 0; i < 16; i++, a += i & 1 ? 8 : 2040) {
    const uint2 x = lds64(a);
    asm volatile("st.shared.v2.u32 [%0], {%1, %2};" ::"r"(a), "r"(scale_f16(x.x, f0)), "r"(scale_f16(x.y, f1)) : "memory");
  }
}
__device__ __forceinline__ uint32_t k_scale(uint32_t s) { return bf2_fma(s, 0x40D540D5u, bf2_mul(s, 0x3BEE3BEEu)); }
__device__ __forceinline__ uint32_t k_zero(uint32_t z) { return bf2_mul(z, 0xBC80BC80u); }
__device__ __forceinline__ uint32_t k_pair(uint32_t x, uint32_t xs, uint32_t z, uint32_t s, uint32_t off) {
  return bf2_fma(bf2_fma(x, xs, z), s, off);
}
constexpr uint32_t kByteScaleK = 0x7F007F00u, kBf16ScaleK = 0x3C803C80u, kByteScaleV = 0x60006000u;
template <bool kIsV>
__device__ __forceinline__ void load_unit(const Params& p, int row0, uint32_t t, Unit& d) {
  const uint32_t hi = t >= 48 ? 1 : 0, q = t - hi * 48;
  const uint8_t* src = (const uint8_t*)((kIsV ? p.qv : p.qk) + (size_t)row0 * kD) + (hi * 3072 + q * 16);
#pragma unroll
  for (int i = 0; i < 4; i++) d.x[i] = ldg128_last_use(src + i * 768);
  if (kIsV) {
    uint32_t o = hi * 8;
    asm("" : "+r"(o));
    d.s = ldg64((const uint8_t*)(p.vs + row0) + o);
    d.z = ldg64((const uint8_t*)(p.vz + row0) + o);
  } else {
    d.s = ldg64((const uint8_t*)(p.ks + (row0 / kGroupTok) * kD) + q * 8);
    d.z = ldg64((const uint8_t*)(p.kz + (row0 / kGroupTok) * kD) + q * 8);
  }
}
__device__ __forceinline__ bool codes_are_bytes(const Unit& d, uint32_t a = 0) {
#pragma unroll
  for (int i = 0; i < 4; i++) a |= d.x[i].x | d.x[i].y | d.x[i].z | d.x[i].w;
  return !__any_sync(0xffffffffu, a > 255);
}
template <int kHalf>
__device__ __forceinline__ uint32_t dup16(uint32_t w) {
  uint32_t v;
  if (kHalf == 0) asm("{\n.reg .b16 a, b;\nmov.b32 {a, b}, %1;\nmov.b32 %0, {a, a};\n}" : "=r"(v) : "r"(w));
  else asm("{\n.reg .b16 a, b;\nmov.b32 {a, b}, %1;\nmov.b32 %0, {b, b};\n}" : "=r"(v) : "r"(w));
  return v;
}
template <bool kIsV>
__device__ __forceinline__ uint64_t unit_dst(const Params& p, int step, int grp, int mt, uint32_t t, int own = kSteps) {
  const uint32_t hi = t >= 48 ? 1 : 0, q = t - hi * 48;
  return (uint64_t)(tile_image(p, step, grp, kIsV && step < own) + mt * (kIsV ? 3072 : 1024)) +
         ((q >> 4) * (kIsV ? 1024 : kChunkBytes) + hi * 512 + (q & 1) * 8 + ((((q & 15) >> 1) ^ (hi * 4)) << 4));
}
__device__ __forceinline__ void store_k(uint64_t dst, int slot, uint32_t t, const Unit& d, uint32_t bars, bool bytes) {
  const uint2 off = lds64(bars + kOffK + slot * (kD * 2) + (t >= 48 ? t - 48 : t) * 8);
  uint32_t x[8];
  if (bytes) {
#pragma unroll
    for (int i = 0; i < 4; i++) {
      x[2 * i] = d.x[i].y * 65536u + d.x[i].x;
      x[2 * i + 1] = d.x[i].w * 65536u + d.x[i].z;
    }
  } else {
#pragma unroll
    for (int i = 0; i < 4; i++) {
      x[2 * i] = codes_bf16(d.x[i].x, d.x[i].y);
      x[2 * i + 1] = codes_bf16(d.x[i].z, d.x[i].w);
    }
  }
  const uint32_t xs = bytes ? kByteScaleK : kBf16ScaleK;
  const uint32_t s0 = k_scale(d.s.x), s1 = k_scale(d.s.y), z0 = k_zero(d.z.x), z1 = k_zero(d.z.y);
#pragma unroll
  for (int i = 0; i < 4; i++)
    stg64((dst ^ (i * 16)) + i * 128, k_pair(x[2 * i], xs, z0, s0, off.x), k_pair(x[2 * i + 1], xs, z1, s1, off.y));
}
constexpr uint32_t kCentreBits = 512 * 0x10001u;
constexpr float kCentre = 512 * (1.f / 16777216);
__device__ __forceinline__ void store_v(uint64_t dst, int step, const Unit& d, uint32_t bars) {
  const uint2 par = lds64(bars + kParV + (step >> 4) * 32);
  const float alpha = __uint_as_float(par.x), centre = __uint_as_float(par.y ^ (step & 8) << 28);
#pragma unroll
  for (int i = 0; i < 4; i++) {
    const uint32_t zw = i < 2 ? d.z.x : d.z.y, sw = i < 2 ? d.s.x : d.s.y;
    const uint32_t zz = (i & 1) ? dup16<1>(zw) : dup16<0>(zw), ss = (i & 1) ? dup16<1>(sw) : dup16<0>(sw);
    auto pair = [&](uint32_t a, uint32_t b) {
      uint32_t v;
      asm("{\n.reg .b32 t;\nsub.rn.bf16x2 t, %1, %2;\nmul.rn.bf16x2 %0, t, %3;\n}"
          : "=r"(v)
          : "r"(codes_bf16(a, b)), "r"(zz), "r"(ss));
      return pack_f16(fmaf(bf_lo(v), alpha, centre), fmaf(bf_hi(v), alpha, centre));
    };
    stg64((dst ^ (i * 16)) + i * 128, pair(d.x[i].x, d.x[i].y), pair(d.x[i].z, d.x[i].w));
  }
}
__device__ __forceinline__ void store_v_any(uint64_t dst, int step, const Unit& d, uint32_t bars) {
  const uint2 par = lds64(bars + kParV + (step >> 4) * 32 + 16);
  const uint32_t z0 = d.z.x - 0x40004000u, z1 = d.z.y - 0x40004000u;
  if (!codes_are_bytes(d, ((z0 | z1) & 0xFC00FC00u) | ((d.s.x | d.s.y) & 0x80008000u)) || par.x == 0) {
    store_v(dst, step, d, bars);
    return;
  }
  const uint2 z = make_uint2(z0 * 8 + 0x84008400u, z1 * 8 + 0x84008400u);
  const uint2 s = make_uint2(h2_mul(d.s.x * 8 + par.y, par.x), h2_mul(d.s.y * 8 + par.y, par.x));
  const uint32_t c2 = kCentreBits ^ (step & 8) * 0x10001000u;
#pragma unroll
  for (int i = 0; i < 4; i++) {
    const uint32_t zw = i < 2 ? z.x : z.y, sw = i < 2 ? s.x : s.y;
    const uint32_t zz = (i & 1) ? dup16<1>(zw) : dup16<0>(zw), ss = (i & 1) ? dup16<1>(sw) : dup16<0>(sw);
    stg64((dst ^ (i * 16)) + i * 128, h2_fma(h2_fma(d.x[i].y * 65536u + d.x[i].x, kByteScaleV, zz), ss, c2),
          h2_fma(h2_fma(d.x[i].w * 65536u + d.x[i].z, kByteScaleV, zz), ss, c2));
  }
}
struct Stat { uint4 s[4], z[4]; };
struct Range { uint4 lo; uint32_t hi; };
__device__ __forceinline__ void stat_load(const Params& p, int head, int j, uint32_t lane, Stat& d) {
  const bool v = lane >= 24;
  const uint32_t off = v ? (head * kS + j * 256) * 2 + (lane - 24) * 16 : (head * 32 + j * 4) * (kD * 2) + lane * 16;
  const uint32_t step = v ? 128 : kD * 2;
  const uint8_t *ps = (const uint8_t*)(v ? p.vs : p.ks), *pz = (const uint8_t*)(v ? p.vz : p.kz);
#pragma unroll
  for (int i = 0; i < 4; i++) {
    uint32_t o = off + i * step;
    asm("" : "+r"(o));
    d.s[i] = ldg128(ps + o);
    d.z[i] = ldg128(pz + o);
  }
}
__device__ __forceinline__ uint32_t range2(uint32_t s, uint32_t z) {
  uint32_t r;
  asm("{\n.reg .b32 m;\nmax.xorsign.abs.bf16x2 m, %2, %3;\nmul.rn.bf16x2 %0, %1, m;\n}"
      : "=r"(r)
      : "r"(s), "r"(z), "r"(0x3F803F80u));
  return r & 0x7fff7fffu;
}
__device__ __forceinline__ void stat_add(const Stat& d, Range& r) {
  auto col = [&](uint32_t& lo, uint32_t a, uint32_t b, uint32_t c, uint32_t e) {
    lo = __vimin3_u16x2(__vimin3_u16x2(lo, a, b), c, e);
    r.hi = __vimax3_u16x2(__vimax3_u16x2(r.hi, a, b), c, e);
  };
  col(r.lo.x, range2(d.s[0].x, d.z[0].x), range2(d.s[1].x, d.z[1].x), range2(d.s[2].x, d.z[2].x), range2(d.s[3].x, d.z[3].x));
  col(r.lo.y, range2(d.s[0].y, d.z[0].y), range2(d.s[1].y, d.z[1].y), range2(d.s[2].y, d.z[2].y), range2(d.s[3].y, d.z[3].y));
  col(r.lo.z, range2(d.s[0].z, d.z[0].z), range2(d.s[1].z, d.z[1].z), range2(d.s[2].z, d.z[2].z), range2(d.s[3].z, d.z[3].z));
  col(r.lo.w, range2(d.s[0].w, d.z[0].w), range2(d.s[1].w, d.z[1].w), range2(d.s[2].w, d.z[2].w), range2(d.s[3].w, d.z[3].w));
}
__device__ __forceinline__ void sts128(uint32_t a, uint32_t x, uint32_t y, uint32_t z, uint32_t w) {
  asm volatile("st.shared.v4.u32 [%0], {%1, %2, %3, %4};" ::"r"(a), "r"(x), "r"(y), "r"(z), "r"(w) : "memory");
}
__device__ __forceinline__ uint4 stat_finish(const Range& r, uint32_t lane) {
  const bool v = lane >= 24;
  const uint32_t lo = __vimin3_u16x2(__vminu2(r.lo.x, r.lo.y), r.lo.z, r.lo.w);
  const float amin = bf_hi(__reduce_min_sync(0xffffffffu, v ? min(lo, lo << 16) : ~0u));
  const float amax = fmaxf(bf_hi(__reduce_max_sync(0xffffffffu, v ? max(r.hi, r.hi << 16) : 0u)), 1e-30f);
  const bool centred = amax <= 2.f * amin && amax <= 1e30f;
  const uint32_t a15 = __float_as_uint(__fdividef(centred ? 0.98f * kCentre * 32768 : 16.f * 32768, amax)) & 0xFFFFE000u;
  const float alpha = __uint_as_float(a15) * (1.f / 32768);
  if (lane == 24)
    return make_uint4(__float_as_uint(alpha), centred ? __float_as_uint(kCentre) : 0u, __float_as_uint(__fdividef(1.f, alpha)), 0u);
  if (v) return make_uint4(centred ? (0x3C00u | (a15 >> 13 & 0x3FFu)) * 0x10001u : 0u, ((a15 >> 23) - 239u) * 0x4000400u, 0u, 0u);
  return make_uint4(bf2_mul(r.lo.x, kOffsetFactor), bf2_mul(r.lo.y, kOffsetFactor), bf2_mul(r.lo.z, kOffsetFactor),
                    bf2_mul(r.lo.w, kOffsetFactor));
}
__device__ __forceinline__ void stat_keep(const uint4& x, int wave, uint32_t lane, uint32_t bars) {
  if (lane < 26)
    sts128(bars + lane * 16 + (lane < 24 ? kOffK + (wave & 1) * (kD * 2) : kParV - 24 * 16 + wave * 32), x.x, x.y, x.z, x.w);
}
__device__ __forceinline__ void prefetch_bulk(const void* g, uint32_t bytes) {
  asm volatile("cp.async.bulk.prefetch.L2.global [%0], %1;" ::"l"(g), "r"(bytes) : "memory");
}
__device__ __forceinline__ void publish(const Params& p, int flag, int grp) {
  __syncwarp();
  asm volatile(
      "{\n.reg .pred p;\nelect.sync _|p, 0xffffffff;\n@p red.release.gpu.global.add.u32 [%0], 1;\n}" ::"l"(
          p.flags + grp * kFlagsPerGroup + flag)
      : "memory");
}
__device__ __forceinline__ void flag_wait(const unsigned* f) {
#pragma unroll 1
  for (int n = 0; n < kFlagPolls; n++) {
    unsigned v;
    asm volatile("ld.acquire.gpu.global.u32 %0, [%1];" : "=r"(v) : "l"(f) : "memory");
    if (__all_sync(0xffffffffu, v >= kFlagTarget)) break;
  }
  asm volatile("fence.proxy.async.global;" ::: "memory");
}

__device__ __forceinline__ void helper_cta(const Params& p, const CUtensorMap& tmq, uint32_t sbase, uint32_t t_start) {
  constexpr int kFullQ = 0, kEmptyQ = 32, kDone = 64, kFullK = 72;
  const uint32_t bars = sbase + kSmemBar, sq = sbase + kMaxTail * kTileBytes;
  const int warp = __shfl_sync(0xffffffffu, threadIdx.x >> 5, 0);
  const int lane = threadIdx.x & 31;
  const int grp0 = blockIdx.x - kOwners;
  auto job_grp = [&](int n) { return (int)(kJobs >> (16 * n + 4 * grp0) & 7); };
  auto job_row = [&](int n) { return ((kWaves - 1) * 8 + job_grp(n)) * kS; };
  auto job_images = [&](int n) { return p.prob + (size_t)(kHelperImages + job_grp(n) * (kMaxTail * kTileBytes)); };
  if (threadIdx.x == 0) {
    for (int i = 0; i < 3; i++) {
      mbar_init(bars + kFullQ + 8 * i, 1);
      mbar_init(bars + kEmptyQ + 8 * i, 4);
    }
    mbar_init(bars + kDone, 8);
    mbar_init(bars + kFullK, 1);
    asm volatile("fence.proxy.async.shared::cta;" ::: "memory");
  }
  auto sleep_until = [&](uint32_t t) {
    while (now_clk() - t_start < t) __nanosleep(200);
  };
  auto wait_long = [&](uint32_t bar, uint32_t parity) {
#pragma unroll 1
    for (int k = 0; k < kFlagPolls && !mbar_try(bar, parity); k++) __nanosleep(200);
  };
  sleep_until(kHelperPrepare);
  if (warp < 6) {
    const int head = job_row(warp & 1) / kS - (warp >> 1) * 8, blocks = tail_blocks(head & 7);
    if (warp < 2 && elect_one()) prefetch_bulk(p.qk + (size_t)(head * kS + kS - blocks * kBN) * kD, blocks * 2 * kTileBytes);
    __syncwarp();
    Range r = {make_uint4(~0u, ~0u, ~0u, ~0u), 0u};
#pragma unroll 1
    for (int j = 0; j < 8; j += 2) {
      Stat a, b;
      stat_load(p, head, j, lane, a);
      stat_load(p, head, j + 1, lane, b);
      stat_add(a, r);
      stat_add(b, r);
    }
    const uint4 x = stat_finish(r, lane);
    if (warp < 2) stat_keep(x, warp, lane, bars);
    *(uint4*)(p.prob + kHeadStats + head * 512 + lane * 16) = x;
  }
  __syncthreads();
  if (threadIdx.x < 2)
    asm volatile("red.release.gpu.global.add.u32 [%0], %1;" ::"l"(p.flags + kFlagStats + job_grp(threadIdx.x)), "n"(kFlagTarget)
                 : "memory");
#pragma unroll 1
  for (int n = 0; n < 2; n++) {
    const int team = warp / 3, units = 16 * tail_blocks(job_grp(n));
    const uint32_t t = threadIdx.x - team * 96, hi = t >= 48 ? 1 : 0, q = t - hi * 48;
    const int row = job_row(n) + kS - units * 8;
    const uint64_t dst = (uint64_t)job_images(n) +
                         ((q >> 4) * kChunkBytes + hi * 512 + (q & 1) * 8 + ((((q & 15) >> 1) ^ (hi * 4)) << 4));
    auto unit_at = [&](int m) { return (m >> 4) * kTileBytes + (m & 15) * 1024; };
#pragma unroll 1
    for (int m = 4 * team; m < units; m += 16) {
      Unit u[4];
#pragma unroll
      for (int i = 0; i < 4; i++) load_unit<false>(p, row + (m + i) * 8, t, u[i]);
#pragma unroll
      for (int i = 0; i < 4; i++) store_k(dst + unit_at(m + i), n, t, u[i], bars, codes_are_bytes(u[i]));
    }
  }
  __threadfence();
  __syncthreads();
  if (warp >= 8) {
    asm volatile("setmaxnreg.dec.sync.aligned.u32 104;");
    if (warp == 8) {
      sleep_until(kHelperDelay);
      uint32_t slot = 0, parity = 1;
#pragma unroll 1
      for (int z = 0; z < 64; z++) {
        const int n = z >> 5, blocks = tail_blocks(job_grp(n));
        if (z == 0 || z == 35) {
          if (n) mbar_spin(bars + kDone, 0);
          asm volatile("fence.proxy.async.global;" ::: "memory");
          if (elect_one()) {
            mbar_expect_tx(bars + kFullK, blocks * kTileBytes);
            bulk_load(sbase, job_images(n), blocks * kTileBytes, bars + kFullK);
          }
          __syncwarp();
        }
        const int half = blocks == 1 ? (z & 28) + (z & 1) * 2 + ((z >> 1) & 1) : z & 31;
        const uint32_t bar = bars + kFullQ + 8 * slot;
        mbar_spin(bars + kEmptyQ + 8 * slot, parity);
        if (elect_one()) {
          mbar_expect_tx(bar, kTileBytes / 2);
#pragma unroll
          for (int c = 0; c < 3; c++)
            tma_load_2d(sq + slot * (kTileBytes / 2) + c * 8192, &tmq, c * 64, job_row(n) + half * 64, bar);
          const int v = min(z + 2 * 3, 63);
          prefetch_bulk(p.q + (size_t)(job_row(v >> 5) + (v & 31) * 64) * kD, kTileBytes / 2);
          if (z == 24) prefetch_bulk(job_images(1), tail_blocks(job_grp(1)) * kTileBytes);
        }
        __syncwarp();
        if (++slot == 3) {
          slot = 0;
          parity ^= 1;
        }
      }
    } else if (warp == 9) {
#pragma unroll 1
      for (int n = 0; n < 2; n++) {
        wait_long(bars + kDone, n);
        if (elect_one()) {
          asm volatile("red.release.gpu.global.add.u32 [%0], %1;" ::"l"(p.flags + kFlagHelper + job_grp(n)), "n"(kFlagTarget)
                       : "memory");
        }
        __syncwarp();
      }
    }
    return;
  }
  asm volatile("setmaxnreg.inc.sync.aligned.u32 200;");
  const int wg = warp >> 2;
  float A[64], B[64];
#pragma unroll
  for (int i = 0; i < 64; i++) asm volatile("" : "=f"(A[i]), "=f"(B[i]));
  int n, blocks;
  auto issue = [&](float (&S)[64], int tile, int j) {
    const uint32_t z = 32 * n + (blocks == 1 ? (tile >> 1) * 4 + 2 * wg + (tile & 1) : 2 * tile + wg);
    const uint32_t turn = z * 43 >> 7, slot = z - 3 * turn;
    if (j == 0) mbar_wait(bars + kFullQ + 8 * slot, turn & 1);
    const uint32_t kb = desc_lo(sbase, 16) + j * (kTileBytes >> 4);
    const uint32_t qb = desc_lo(sq, 16) + slot * (kTileBytes >> 5);
    bar_sync(2 + wg);
    wg_fence();
    wgmma_new_n128(S, desc64<1024>(qb), desc64<1024>(kb));
#pragma unroll
    for (int kk = 1; kk < 12; kk++)
      wgmma_ss_n128(S, desc64<1024>(qb + (kk >> 2) * 512 + (kk & 3) * 2), desc64<1024>(kb + (kk >> 2) * 1024 + (kk & 3) * 2), 1);
    wg_commit();
    bar_arrive(3 - wg);
    return bars + kEmptyQ + 8 * slot;
  };
  float r0, r1;
  auto finish = [&](float (&S)[64], int tile, int j) {
    pin(S);
    int a0 = 0, a1 = 0;
    uint32_t u0 = ~0u, u1 = ~0u;
#pragma unroll
    for (int i = 0; i < 64; i += 4) {
      a0 = __vimax3_s32(a0, __float_as_int(S[i]), __float_as_int(S[i + 1]));
      a1 = __vimax3_s32(a1, __float_as_int(S[i + 2]), __float_as_int(S[i + 3]));
      if (i < 16) {
        u0 = __vimin3_u32(u0, __float_as_uint(S[i]), __float_as_uint(S[i + 1]));
        u1 = __vimin3_u32(u1, __float_as_uint(S[i + 2]), __float_as_uint(S[i + 3]));
      }
    }
    uint8_t* out = p.prob + (size_t)((job_grp(n) * 16 + tile) * kProbBytes);
    float d0 = 0.f, d1 = 0.f;
    if (j == 0) r0 = r1 = 0.f;
    if (__any_sync(0xffffffffu, max(a0, a1) > __float_as_int(kLazyAbove) || max(u0, u1) >= __float_as_uint(-kLazyBelow))) {
      r0 = -INFINITY;
      d0 = S[0];
      d1 = S[2];
#pragma unroll
      for (int i = 0; i < 64; i += 4) {
        d0 = fmaxf(d0, fmaxf(S[i], S[i + 1]));
        d1 = fmaxf(d1, fmaxf(S[i + 2], S[i + 3]));
      }
      d0 = fmaxf(d0, __shfl_xor_sync(0xffffffffu, d0, 1));
      d1 = fmaxf(d1, __shfl_xor_sync(0xffffffffu, d1, 1));
      d0 = fmaxf(d0, __shfl_xor_sync(0xffffffffu, d0, 2));
      d1 = fmaxf(d1, __shfl_xor_sync(0xffffffffu, d1, 2));
#pragma unroll
      for (int i = 0; i < 64; i++) S[i] -= (i & 2) ? d1 : d0;
    }
    float l0 = 0.f, l1 = 0.f;
#pragma unroll
    for (int i = 0; i < 64; i += 4) {
#pragma unroll
      for (int k = 0; k < 4; k++) S[i + k] = ex2(S[i + k]);
      l0 += S[i] + S[i + 1];
      l1 += S[i + 2] + S[i + 3];
    }
    pin(S);
    l0 += __shfl_xor_sync(0xffffffffu, l0, 1);
    l1 += __shfl_xor_sync(0xffffffffu, l1, 1);
    l0 += __shfl_xor_sync(0xffffffffu, l0, 2);
    l1 += __shfl_xor_sync(0xffffffffu, l1, 2);
    uint8_t* dst = out + kProbData + (2 * j + wg) * 16384 + (threadIdx.x & 127) * 16;
#pragma unroll
    for (int i = 0; i < 8; i++)
      asm volatile("st.global.L1::no_allocate.v4.u32 [%0], {%1, %2, %3, %4};" ::"l"(dst + i * 2048),
                   "r"(pack_f16(S[8 * i], S[8 * i + 1])), "r"(pack_f16(S[8 * i + 2], S[8 * i + 3])),
                   "r"(pack_f16(S[8 * i + 4], S[8 * i + 5])), "r"(pack_f16(S[8 * i + 6], S[8 * i + 7]))
                   : "memory");
    l0 *= 0.25f;
    l1 *= 0.25f;
    r0 += l0;
    r1 += l1;
    if ((lane & 3) == 0) {
      *(float4*)(out + kProbExtra + j * 1024 + threadIdx.x * 4) = make_float4(d0, d1, l0, l1);
      if (j == blocks - 1) stg64((uint64_t)(out + threadIdx.x * 2), __float_as_uint(r0), __float_as_uint(r1));
    }
  };
  if (wg == 1) bar_arrive(2);
#pragma unroll 1
  for (n = 0; n < 2; n++) {
    blocks = tail_blocks(job_grp(n));
    wait_long(bars + kFullK, n);
    int tile = 0, j = 0, tile_b = -1, j_b = 0;
#pragma unroll 1
    for (;;) {
      const uint32_t qa = issue(A, tile, tile < 16 ? j : 1);
      wg_wait<1>();
      if (tile_b >= 0) finish(B, tile_b, j_b);
      wg_wait<0>();
      if (tile == 16) break;
      const bool wrap = j == blocks - 1;
      if (wrap && lane == 0) mbar_arrive_local(qa);
      tile_b = tile + wrap;
      j_b = wrap ? 0 : j + 1;
      const uint32_t qb = issue(B, tile_b, j_b);
      wg_wait<1>();
      finish(A, tile, j);
      asm volatile("st.volatile.shared.f32 [%0], %1;" ::"r"(bars + kDummy), "f"(r1) : "memory");
      wg_wait<0>();
      const bool wrap_b = j_b == blocks - 1;
      if (wrap_b && lane == 0) mbar_arrive_local(qb);
      tile = tile_b + wrap_b;
      j = wrap_b ? 0 : j_b + 1;
    }
    __syncwarp();
    if (lane == 0) mbar_arrive_local(bars + kDone);
  }
}

__global__ void __cluster_dims__(2, 1, 1) __launch_bounds__(384, 1)
    attn_kernel(const Params p, const __grid_constant__ CUtensorMap tmq, const __grid_constant__ CUtensorMap tmo) {
  extern __shared__ uint8_t smem_raw[];
  const uint32_t t_start = now_clk();
  const uint32_t sbase = ((uint32_t)__cvta_generic_to_shared(smem_raw) + 1023) & ~1023u;
  if (blockIdx.x >= kOwners) {
    helper_cta(p, tmq, sbase, t_start);
    return;
  }
  const uint32_t bars = sbase + kSmemBar;
  const int grp = blockIdx.x >> 4, mt = blockIdx.x & 15;
  const int tail = __shfl_sync(0xffffffffu, tail_blocks(grp), 0), own = kSteps - tail;
  const uint32_t tail_stage = tail == 3 ? kSmemQ : kSmemV + kTileBytes;
  const int warp = __shfl_sync(0xffffffffu, threadIdx.x >> 5, 0);
  const int lane = threadIdx.x & 31;

  auto load_q = [&](int tile, int w) {
    const uint32_t bar = bars + kBarFullQ + 8 * w;
    const int row = (tile * 8 + grp) * kS + mt * 128 + w * 64;
    mbar_expect_tx(bar, 16384);
    mbar_expect_tx(bars + kBarFullQ2 + 8 * w, 8192);
#pragma unroll
    for (int c = 0; c < 3; c++)
      tma_load_2d(sbase + kSmemQ + w * 24576 + c * 8192, &tmq, c * 64, row, c < 2 ? bar : bars + kBarFullQ2 + 8 * w);
  };
  if (warp == 8 && elect_one()) {
    mbar_init(bars + kBarParams, 1);
    mbar_init(bars + kBarCodes, 1);
    mbar_init(bars + kBarUnits, 1);
    asm volatile("fence.proxy.async.shared::cta;" ::: "memory");
    mbar_expect_tx(bars + kBarParams, 32768);
    bulk_load(sbase + kSmemV, p.ks + grp * 32 * kD, 12288, bars + kBarParams);
    bulk_load(sbase + kSmemV + 12288, p.kz + grp * 32 * kD, 12288, bars + kBarParams);
    bulk_load(sbase + kSmemV + 24576, p.vs + grp * kS, 4096, bars + kBarParams);
    bulk_load(sbase + kSmemV + 36864, p.vz + grp * kS, 4096, bars + kBarParams);
  }
  __syncwarp();
  if (warp == 8) {
    asm volatile("bar.arrive 6, 160;" ::: "memory");
    while (now_clk() - t_start < ((uint32_t)(kCodeDelays >> 8 * grp) & 255) * 32) {}
  }
  const int row_k0 = grp * kS + (blockIdx.x & 1) * 64;
  if (warp == 8 && elect_one()) {
    mbar_expect_tx(bars + kBarUnits, 4 * 6144);
#pragma unroll
    for (int j = 0; j < 4; j++)
      bulk_load(sbase + kSmemK + 3 * kChunkBytes + j * 6144,
                (j & 1 ? p.qv : p.qk) + (size_t)unit_row((j >> 1) + 1 - (j & 1), grp, mt) * kD, 6144, bars + kBarUnits);
    mbar_expect_tx(bars + kBarCodes, kTileBytes);
    bulk_load(sbase + kSmemV + kTileBytes, p.qk + (size_t)row_k0 * kD, kTileBytes, bars + kBarCodes);
    for (int i = 0; i < 2; i++) {
      mbar_init(bars + kBarFullK01 + 8 * i, 1);
      mbar_init(bars + kBarFullV + 8 * i, 1);
      mbar_init(bars + kBarEmptyK12 + 8 * i, 16);
      mbar_init(bars + kBarEmptyV + 8 * i, 16);
      mbar_init(bars + kBarFullQ + 8 * i, 1);
      mbar_init(bars + kBarFullQ2 + 8 * i, 1);
      mbar_init(bars + kBarEmptyQ + 8 * i, 4);
      mbar_init(bars + kBarStage + 8 * i, 4);
      mbar_init(bars + kBarStaged + 8 * i, 4);
      for (int c = 0; c < 3; c++) mbar_init(bars + kBarTail + 24 * i + 8 * c, 4);
    }
    mbar_init(bars + kBarFullK2, 1);
    mbar_init(bars + kBarFullV2, 1);
    mbar_init(bars + kBarEmptyK0, 16);
    asm volatile("st.shared.u32 [%0], %1;" ::"r"(bars + kProgress), "r"(0) : "memory");
    asm volatile("fence.mbarrier_init.release.cluster;" ::: "memory");
    asm volatile("fence.acq_rel.cta;" ::: "memory");
    asm volatile("prefetch.tensormap [%0];" ::"l"(&tmq) : "memory");
  }
  __syncwarp();
  cluster_arrive();
  const bool helper = warp > 8 || (warp >= 4 && warp < 7);
  const uint32_t th = warp < 8 ? threadIdx.x & 127 : threadIdx.x - 288;
  const int it = warp < 8 ? 1 : 0;
  if (warp == 8) {
    while (now_clk() - t_start < ((uint32_t)(kQueryDelays >> 8 * grp) & 255) * 32) {}
#pragma unroll 1
    for (int w = 0; w < 2; w++)
      if (elect_one()) load_q(0, w);
  }
  __syncwarp();
  if (warp < 4) {
    asm volatile("bar.sync 6, 160;" ::: "memory");
    Range r = {make_uint4(~0u, ~0u, ~0u, ~0u), 0u};
    mbar_spin(bars + kBarParams, 0);
    const uint32_t pitch = lane >= 24 ? 128 : kD * 2;
    uint32_t src = sbase + kSmemV + (lane >= 24 ? 24576 - 384 : 0) + lane * 16 + warp * 8 * pitch;
#pragma unroll 1
    for (int j = 0; j < 2; j++) {
      Stat st;
#pragma unroll
      for (int i = 0; i < 4; i++, src += pitch) {
        st.s[i] = lds128(src);
        st.z[i] = lds128(src + 12288);
      }
      stat_add(st, r);
    }
    const uint32_t part = sbase + kSmemV + 40960 + lane * 16;
    sts128(part + warp * 1024, r.lo.x, r.lo.y, r.lo.z, r.lo.w);
    sts128(part + warp * 1024 + 512, r.hi, 0u, 0u, 0u);
    asm volatile("bar.sync 4, 128;" ::: "memory");
#pragma unroll
    for (int j = 1; j < 4; j++) {
      const uint32_t other = part + ((warp + j) & 3) * 1024;
      const uint4 lo = lds128(other);
      r.lo = make_uint4(__vminu2(r.lo.x, lo.x), __vminu2(r.lo.y, lo.y), __vminu2(r.lo.z, lo.z), __vminu2(r.lo.w, lo.w));
      r.hi = __vmaxu2(r.hi, lds64(other + 512).x);
    }
    stat_keep(stat_finish(r, lane), 0, lane, bars);
    __syncwarp();
    if (warp == 0) asm volatile("bar.arrive 5, 224;" ::: "memory");
  }
  if (helper) {
    asm volatile("bar.sync 5, 224;" ::: "memory");
    const uint32_t hi = th >= 48 ? 1 : 0, q = th - hi * 48;
    const uint32_t src = sbase + kSmemK + 3 * kChunkBytes + it * 12288 + hi * 3072 + q * 16;
    const uint32_t kp = sbase + kSmemV + (2 * it + 2 + (mt >> 3)) * (kD * 2) + q * 8;
    const uint32_t vp = sbase + kSmemV + 24576 + (it * kBN + mt * 8 + hi * 4) * 2;
    Unit k0, v0;
    k0.s = lds64(kp);
    k0.z = lds64(kp + 12288);
    v0.s = lds64(vp);
    v0.z = lds64(vp + 12288);
    mbar_spin(bars + kBarUnits, 0);
#pragma unroll
    for (int i = 0; i < 4; i++) {
      k0.x[i] = lds128(src + i * 768);
      v0.x[i] = lds128(src + 6144 + i * 768);
    }
    store_k(unit_dst<false>(p, it + 1, grp, mt, th), 0, th, k0, bars, false);
    store_v(unit_dst<true>(p, it, grp, mt, th), it, v0, bars);
    if (warp < 8) asm volatile("bar.arrive 3, 192;" ::: "memory");
  }
  cluster_wait();
  if (warp < 4) {
    uint2 o0[3], s0[3], z0[3];
#pragma unroll
    for (int c = 0; c < 3; c++) {
      const uint32_t col = c * 128 + (threadIdx.x & 15) * 8;
      o0[c] = lds64(bars + kOffK + col);
      s0[c] = lds64(sbase + kSmemV + (blockIdx.x & 1) * (kD * 2) + col);
      z0[c] = lds64(sbase + kSmemV + 12288 + (blockIdx.x & 1) * (kD * 2) + col);
      s0[c] = make_uint2(k_scale(s0[c].x), k_scale(s0[c].y));
      z0[c] = make_uint2(k_zero(z0[c].x), k_zero(z0[c].y));
    }
    mbar_spin(bars + kBarCodes, 0);
    const uint32_t r = threadIdx.x >> 4, half = sbase + kSmemK + (blockIdx.x & 1) * (kChunkBytes / 2);
    uint32_t src = sbase + kSmemV + kTileBytes + r * 768 + (threadIdx.x & 15) * 16;
    uint32_t dst = half + r * 128 + (threadIdx.x & 1) * 8 + ((((threadIdx.x & 15) >> 1) ^ r) << 4);
#pragma unroll 1
    for (int i = 0; i < 4; i++, src += 16 * 768, dst += 2048) {
      uint4 x[6];
#pragma unroll
      for (int j = 0; j < 6; j++)
        asm volatile("ld.shared.v4.u32 {%0, %1, %2, %3}, [%4];"
                     : "=r"(x[j].x), "=r"(x[j].y), "=r"(x[j].z), "=r"(x[j].w)
                     : "r"(src + (j & 1) * 8 * 768 + (j >> 1) * 256));
#pragma unroll
      for (int j = 0; j < 6; j++)
        asm volatile("st.shared.v2.u32 [%0], {%1, %2};" ::"r"(dst + (j & 1) * 1024 + (j >> 1) * kChunkBytes),
                     "r"(k_pair(codes_bf16(x[j].x, x[j].y), kBf16ScaleK, z0[j >> 1].x, s0[j >> 1].x, o0[j >> 1].x)),
                     "r"(k_pair(codes_bf16(x[j].z, x[j].w), kBf16ScaleK, z0[j >> 1].y, s0[j >> 1].y, o0[j >> 1].y)));
    }
    asm volatile("fence.proxy.async.shared::cta;" ::: "memory");
    asm volatile("bar.sync 4, 128;" ::: "memory");
    if (threadIdx.x == 0) {
      mbar_expect_tx(bars + kBarFullK01, kChunkBytes);
      mbar_expect_tx(bars + kBarFullK2, kChunkBytes / 2);
#pragma unroll
      for (int c = 0; c < 3; c++)
        bulk_copy_peer(half + c * kChunkBytes, kChunkBytes / 2, bars + (c < 2 ? kBarFullK01 : kBarFullK2),
                       (blockIdx.x & 1) ^ 1);
    }
  }

  if (warp >= 8) {
    asm volatile("setmaxnreg.dec.sync.aligned.u32 56;");
    if (warp == 8) {
      const uint32_t rank = blockIdx.x & 1;
      const unsigned* flags = p.flags + grp * kFlagsPerGroup;
      const uint8_t* const images = tile_image(p, 0, grp, 0);
      auto image = [&](int step, uint32_t offset) { return images + ((step & (kRing - 1)) * (2 * kTileBytes) + offset); };
      uint32_t k_dst = sbase + kSmemK + 2 * kChunkBytes + rank * (kChunkBytes / 2);
      auto next_slot = [&]() {
        k_dst += kChunkBytes;
        if (k_dst >= sbase + kSmemV) k_dst -= 5 * kChunkBytes;
        return k_dst;
      };
      auto k_chunk = [&](uint32_t dst, int step, int c, uint32_t bar) {
        bulk_load_mc(dst, image(step, c * kChunkBytes + rank * (kChunkBytes / 2)), kChunkBytes / 2, bar);
      };
      auto load_k01 = [&](int step) {
        const uint32_t bar = bars + kBarFullK01 + 8 * (step & 1);
        const uint32_t d0 = next_slot(), d1 = next_slot();
        if (elect_one()) {
          mbar_expect_tx(bar, 2 * kChunkBytes);
          k_chunk(d0, step, 0, bar);
          k_chunk(d1, step, 1, bar);
        }
        __syncwarp();
      };
      auto load_k2 = [&](int step) {
        const uint32_t d = next_slot();
        if (elect_one()) {
          mbar_expect_tx(bars + kBarFullK2, kChunkBytes);
          k_chunk(d, step, 2, bars + kBarFullK2);
        }
        __syncwarp();
      };
      auto v_part = [&](int step, uint32_t len, uint32_t bar) {
        bulk_load_mc(sbase + kSmemV + (step & 1) * kTileBytes + rank * (len / 2),
                     image(step, kTileBytes + rank * (len / 2)), len / 2, bar);
      };
      auto load_vt = [&](int step) {
        const uint32_t bar = bars + kBarFullV + 8 * (step & 1);
        if (elect_one()) {
          mbar_expect_tx(bar, kTileBytes);
          v_part(step, kTileBytes, bar);
        }
        __syncwarp();
      };
      auto wait_flag = [&](int f) {
        flag_wait(flags + f);
      };
      auto store_out = [&](int tile, int w) {
        mbar_spin(bars + kBarStaged + 8 * w, tile & 1);
        asm volatile("fence.proxy.async.shared::cta;" ::: "memory");
        if (elect_one()) {
          const int row = (tile * 8 + grp) * kS + mt * 128 + w * 64;
#pragma unroll
          for (int c = 0; c < 3; c++)
            tma_store_2d(&tmo, sbase + kSmemV + w * kTileBytes + kTileBytes / 2 + c * 8192, c * 64, row);
          asm volatile("cp.async.bulk.commit_group;" ::: "memory");
        }
        __syncwarp();
      };
      auto reload_v = [&](int w, int step, uint32_t bar) {
        asm volatile("cp.async.bulk.wait_group.read 0;" ::: "memory");
        if (elect_one())
          bulk_load(sbase + kSmemV + w * kTileBytes + kTileBytes / 2, image(step, kTileBytes + kTileBytes / 2), kTileBytes / 2, bar);
        __syncwarp();
      };
      int pf = 3;
      uint32_t pf_at = unit_row(pf, grp, mt) * (kD * 4);
      auto prefetch_next = [&]() {
        const uint32_t at = pf_at;
        pf++;
        pf_at += (pf & 15) ? kBN * kD * 4 : (kBN + 7 * kS) * kD * 4;
        if (elect_one()) {
          prefetch_bulk((const uint8_t*)p.qv + at, 6144);
          if (pf < own) prefetch_bulk((const uint8_t*)p.qk + pf_at, 6144);
        }
        __syncwarp();
      };
      const uint8_t* prob = p.prob + (size_t)(blockIdx.x * kProbBytes);
      const int poll_step = (own - 3) | 1;
      auto load_p = [&](uint32_t dst, int q, uint32_t bar) {
        bulk_load(dst - rank * (kChunkBytes / 2), prob + kProbData + q * kChunkBytes, kChunkBytes, bar);
      };
      wait_flag(1);
      load_k01(1);
#pragma unroll 1
      for (int s = 0;; s++) {
        const bool newq = (s & 15) == 15;
        if (newq) {
          mbar_spin(bars + kBarEmptyQ, (s >> 4) & 1);
          if (elect_one()) load_q((s >> 4) + 1, 0);
          __syncwarp();
        }
        mbar_spin(bars + kBarEmptyK0, s & 1);
        load_k2(s + 1);
        if (s == 0) {
          if (elect_one()) {
            mbar_expect_tx(bars + kBarFullV, kTileBytes / 2);
            mbar_expect_tx(bars + kBarFullV2, kTileBytes / 2);
            v_part(0, kTileBytes / 2, bars + kBarFullV);
            bulk_load_mc(sbase + kSmemV + kTileBytes / 2 + rank * (kTileBytes / 4),
                         image(0, kTileBytes + kTileBytes / 2 + rank * (kTileBytes / 4)), kTileBytes / 4,
                         bars + kBarFullV2);
          }
          __syncwarp();
          prefetch_next();
        }
        const bool tile_end = (s & 15) == 0 && s > 0;
        if (tile_end) {
          store_out((s >> 4) - 1, 0);
          reload_v(0, s, bars + kBarFullV2);
        }
        const int pf_end = min(s + kLead + 2 + (s >= own - 7), kSteps - 1);
        if (pf < pf_end) prefetch_next();
        if (newq) {
          mbar_spin(bars + kBarEmptyQ + 8, (s >> 4) & 1);
          if (elect_one()) load_q((s >> 4) + 1, 1);
          __syncwarp();
        }
        if (s & 1) {
          uint32_t f = grp * kFlagsPerGroup + s + 2;
          if (lane == 31 && s == kStatStep) f = kFlagStats + grp;
          if (lane == 31 && s == poll_step) f = kFlagHelper + grp;
          f *= 4;
          asm("" : "+r"(f));
          flag_wait((const unsigned*)((const uint8_t*)p.flags + f));
        }
        if (s == poll_step && elect_one()) prefetch_bulk(prob, kProbData + tail * 2 * kChunkBytes);
        __syncwarp();
        mbar_spin(bars + kBarEmptyK12 + 8 * (s & 1), (s >> 1) & 1);
        if (s + 2 < own) {
          load_k01(s + 2);
        } else {
          const uint32_t d0 = next_slot(), d1 = next_slot();
          if (elect_one()) {
            mbar_expect_tx(bars + kBarUnits, 2 * kChunkBytes + 512);
            bulk_load(bars + kOffK, prob, 512, bars + kBarUnits);
            load_p(d0, 0, bars + kBarUnits);
            load_p(d1, 1, bars + kBarUnits);
          }
          __syncwarp();
        }
        mbar_spin(bars + kBarEmptyV + 8 * ((s + 1) & 1), (((s + 1) >> 1) & 1) ^ 1);
        if (newq || tile_end) {
          const uint32_t bar = bars + kBarFullV + 8 * ((s + 1) & 1);
          if (elect_one()) {
            mbar_expect_tx(bar, newq ? kTileBytes / 2 : kTileBytes);
            if (newq) mbar_expect_tx(bars + kBarFullV2, kTileBytes / 2);
            v_part(s + 1, kTileBytes / 2, bar);
          }
          __syncwarp();
          if (tile_end) {
            store_out((s >> 4) - 1, 1);
            reload_v(1, s + 1, bar);
          }
        } else {
          load_vt(s + 1);
        }
        if ((s & 15) == kStatStep && s < kSteps - 16) {
          uint4 x;
          asm volatile("ld.global.L1::no_allocate.v4.u32 {%0, %1, %2, %3}, [%4];"
                       : "=r"(x.x), "=r"(x.y), "=r"(x.z), "=r"(x.w)
                       : "l"(p.prob + (kHeadStats + (((s >> 4) + 1) * 8 + grp) * 512 + lane * 16))
                       : "memory");
          stat_keep(x, (s >> 4) + 1, lane, bars);
          __syncwarp();
        }
        asm volatile("st.volatile.shared.u32 [%0], %1;" ::"r"(bars + kProgress), "r"(s + 1) : "memory");
        if (pf <= pf_end && !tile_end) prefetch_next();
        if (s < kSteps - 16) {
          if ((s & 12) == 8) {
            const uint8_t* qn = (const uint8_t*)(p.q + (size_t)((((s >> 4) + 1) * 8 + grp) * kS + mt * 128) * kD);
            if (elect_one()) prefetch_bulk(qn + (s & 3) * 12288, 12288);
            __syncwarp();
          }
        }
        if (s == own - 2) break;
      }
      wait_flag(kSteps - 1);
      uint32_t vw = pick(tail, kPlacesV<1>, kPlacesV<2>, kPlacesV<3>);
      int q = 2;
#pragma unroll 1
      for (int i = 0;; i++) {
        vw >>= 8;
        const uint32_t bar = bars + (vw >> 1 & 0x78);
        mbar_spin(i == 0 ? bars + kBarEmptyK12 + 8 * ((own - 1) & 1) : bar + (kBarEmptyV - kBarFullV),
                  (i == 0 ? own - 1 : (vw ^ 4) >> 1) >> 1 & 1);
        if (i == 1) mbar_spin(bars + kBarFullQ, 0);
        if (elect_one()) {
          mbar_expect_tx(bar, kTileBytes);
          bulk_load_mc(sbase + (vw & 11) * 16384 + rank * (kTileBytes / 2), image(own + i, rank * (kTileBytes / 2)),
                       kTileBytes / 2, bar);
        }
        __syncwarp();
#pragma unroll 1
        for (; q < min(2 * i + 3, 2 * tail); q++) {
          const uint32_t d = next_slot();
          const uint32_t pb = bars + ((kBarCodes | kBarParams << 8 | (kBarFullQ + 8) << 16 | kBarFullQ2 << 24) >> (8 * q - 16) & 255);
          if (elect_one()) {
            mbar_expect_tx(pb, kChunkBytes);
            load_p(d, q, pb);
          }
          __syncwarp();
        }
        if (i == tail - 1) break;
      }
      unsigned done = 0;
      if (lane == 0)
        asm volatile("atom.global.inc.u32 %0, [%1], %2;" : "=r"(done) : "l"(p.flags + kFlagDone), "n"(kOwners - 1) : "memory");
      if (__shfl_sync(0xffffffffu, done, 0) == kOwners - 1) {
#pragma unroll
        for (int j = 0; j < 8 * kFlagsPerGroup / 128; j++) ((uint4*)p.flags)[j * 32 + lane] = make_uint4(0, 0, 0, 0);
        if (lane < 4) ((uint4*)p.flags)[kFlagHelper / 4 + lane] = make_uint4(0, 0, 0, 0);
      }
      __syncwarp();
      cluster_arrive();
#pragma unroll 1
      for (int j = 0; j < 6; j++) {
        const int w = j >= 3 ? 1 : 0;
        mbar_spin(bars + kBarTail + 8 * j, 0);
        asm volatile("fence.proxy.async.shared::cta;" ::: "memory");
        if (elect_one())
          tma_store_2d(&tmo, sbase + tail_stage + j * 8192, (j - 3 * w) * 64,
                       ((kWaves - 1) * 8 + grp) * kS + mt * 128 + w * 64);
        __syncwarp();
      }
      if (elect_one()) asm volatile("cp.async.bulk.commit_group;\ncp.async.bulk.wait_group.read 0;" ::: "memory");

    } else {
      const uint32_t t = threadIdx.x - 288;
      auto throttle = [&](int i) {
#pragma unroll 1
        for (int n = 0; n < 100000; n++) {
          int prog;
          asm volatile("ld.volatile.shared.u32 %0, [%1];" : "=r"(prog) : "r"(bars + kProgress) : "memory");
          if (__all_sync(0xffffffffu, i <= prog + kLead)) break;
          __nanosleep(200);
        }
      };
      asm volatile("bar.sync 3, 192;" ::: "memory");
      publish(p, 1, grp);
      Unit v, k;
      load_unit<false>(p, unit_row(3, grp, mt), t, k);
      load_unit<true>(p, unit_row(2, grp, mt), t, v);
#pragma unroll 1
      for (int i = 2; i < kSteps; i++) {
        throttle(i - (i >= own));
        if (i + 1 < own) store_k(unit_dst<false>(p, i + 1, grp, mt, t), ((i + 1) >> 4) & 1, t, k, bars, codes_are_bytes(k));
        load_unit<false>(p, unit_row(min(i + 2, own - 1), grp, mt), t, k);
        store_v_any(unit_dst<true>(p, i, grp, mt, t, own), i, v, bars);
        if (i & 1) publish(p, i, grp);
        load_unit<true>(p, unit_row(min(i + 1, kSteps - 1), grp, mt), t, v);
      }
    }
  } else {
    asm volatile("setmaxnreg.inc.sync.aligned.u32 224;");
    const int wg = warp >> 2;
    float S[64], O[96];
    uint32_t P[32];
    float m0 = 0.f, m1 = 0.f, l0 = 0.f, l1 = 0.f, h0 = 0.f, h1 = 0.f;
    bool shifted = false;
    auto release = [&](uint32_t bar) {
      if (lane < 2) mbar_arrive_cluster(bar, lane);
    };
    auto stage_o = [&](uint32_t stage, float f0, float f1, int c_lo, int c_hi) {
      const uint32_t addr = stage + ((warp & 3) * 16 + (lane & 15)) * 128 + (((lane >> 4) ^ (lane & 7)) << 4);
#pragma unroll
      for (int j = 4 * c_lo; j < 4 * c_hi; j++) {
        float* o = O + 8 * j;
#pragma unroll
        for (int i = 0; i < 8; i++) o[i] = (i & 2) ? fmaf(o[i], f1, h1) : fmaf(o[i], f0, h0);
        asm volatile("stmatrix.sync.aligned.m8n8.x4.shared.b16 [%0], {%1, %2, %3, %4};" ::"r"(
                         (addr ^ ((j & 3) * 32)) + (j >> 2) * 8192),
                     "r"(pack_bf16(o[0], o[1])), "r"(pack_bf16(o[2], o[3])), "r"(pack_bf16(o[4], o[5])),
                     "r"(pack_bf16(o[6], o[7]))
                     : "memory");
      }
    };
    auto staged = [&]() {
      __syncwarp();
      if (lane == 0) mbar_arrive_local(bars + kBarStaged + 8 * wg);
    };
    float sc0 = 1.f, sc1 = 1.f;
    auto quad_sum = [&](float x) {
      x += __shfl_xor_sync(0xffffffffu, x, 1);
      return x + __shfl_xor_sync(0xffffffffu, x, 2);
    };
    auto finish_l = [&](int wave, float& i0, float& i1) {
      const uint4 vp = lds128(bars + kParV + wave * 32);
      const float a = quad_sum(l0), b = quad_sum(l1);
      i0 = __uint_as_float(vp.z) * rcp(a);
      i1 = __uint_as_float(vp.z) * rcp(b);
      h0 = (a - 2.f * quad_sum(h0)) * i0 * __uint_as_float(vp.y);
      h1 = (b - 2.f * quad_sum(h1)) * i1 * __uint_as_float(vp.y);
    };
    auto issue_qk = [&](int s, int slot0) {
      const uint32_t kb = desc_lo(sbase + kSmemK, 16);
      const uint32_t qb = desc_lo(sbase + kSmemQ, 16) + wg * 1536;
#pragma unroll
      for (int c = 0; c < 3; c++) {
        const int slot = slot0 + c >= 5 ? slot0 + c - 5 : slot0 + c;
        if (c == 2) {
          mbar_wait(bars + kBarFullK2, s & 1);
          if ((s & 15) == 0) mbar_wait(bars + kBarFullQ2 + 8 * wg, (s >> 4) & 1);
        }
#pragma unroll
        for (int kk = 0; kk < 4; kk++)
          wgmma_ss_n128(S, desc64<1024>(qb + c * 512 + kk * 2), desc64<1024>(kb + slot * 1024 + kk * 2),
                        c + kk > 0);
        if (c != 1) wg_commit();
      }
    };
    auto issue_pv = [&](int s) {
      const uint32_t vb = desc_lo(sbase + kSmemV, 1024) + (s & 1) * (kTileBytes >> 4);
      const int acc = (s & 15) != 0;
      auto run = [&](int lo, int hi, int acc0) {
#pragma unroll
        for (int kk = lo; kk < hi; kk++)
          wgmma_rs_n192t(O, P[kk * 4], P[kk * 4 + 1], P[kk * 4 + 2], P[kk * 4 + 3], desc64<3072>(vb + kk * 384),
                         kk > 0 ? 1 : acc0);
      };
      if (acc) {
        wg_fence();
        run(0, 8, 1);
        wg_commit();
      } else {
        wg_fence();
        run(0, 4, 0);
        mbar_wait(bars + kBarFullV2, (s >> 4) & 1);
        wg_fence();
        run(4, 8, 1);
        wg_commit();
      }
    };
    auto shift = [&](int lo, float d0, float d1) {
#pragma unroll
      for (int i = lo; i < 64; i += 4) {
        S[i] -= d0;
        S[i + 1] -= d0;
        S[i + 2] -= d1;
        S[i + 3] -= d1;
      }
    };
    auto unsafe = [&](int lo, int hi, bool first) {
      int a0 = 0, a1 = 0, b0 = 0, b1 = 0;
#pragma unroll
      for (int i = lo; i < hi; i += 8) {
        a0 = __vimax3_s32(a0, __float_as_int(S[i]), __float_as_int(S[i + 1]));
        a1 = __vimax3_s32(a1, __float_as_int(S[i + 2]), __float_as_int(S[i + 3]));
        b0 = __vimax3_s32(b0, __float_as_int(S[i + 4]), __float_as_int(S[i + 5]));
        b1 = __vimax3_s32(b1, __float_as_int(S[i + 6]), __float_as_int(S[i + 7]));
      }
      bool bad = __vimax3_s32(max(a0, b0), a1, b1) > __float_as_int(kLazyAbove);
      if (first) {
        uint32_t u0 = ~0u, u1 = ~0u;
#pragma unroll
        for (int i = 0; i < 16; i += 4) {
          u0 = __vimin3_u32(u0, __float_as_uint(S[i]), __float_as_uint(S[i + 1]));
          u1 = __vimin3_u32(u1, __float_as_uint(S[i + 2]), __float_as_uint(S[i + 3]));
        }
        bad |= max(u0, u1) >= __float_as_uint(-kLazyBelow);
      }
      return __any_sync(0xffffffffu, bad);
    };
    float e0, e1;
    auto use_true_max = [&](int lo, bool first, bool boundary, float& f0, float& f1) {
      float d0 = S[lo], d1 = S[lo + 2];
#pragma unroll
      for (int i = lo; i < 64; i += 4) {
        d0 = fmaxf(d0, fmaxf(S[i], S[i + 1]));
        d1 = fmaxf(d1, fmaxf(S[i + 2], S[i + 3]));
      }
      d0 = fmaxf(d0, __shfl_xor_sync(0xffffffffu, d0, 1));
      d1 = fmaxf(d1, __shfl_xor_sync(0xffffffffu, d1, 1));
      d0 = fmaxf(d0, __shfl_xor_sync(0xffffffffu, d0, 2));
      d1 = fmaxf(d1, __shfl_xor_sync(0xffffffffu, d1, 2));
      if (!first) {
        d0 = fmaxf(d0, 0.f);
        d1 = fmaxf(d1, 0.f);
        f0 = ex2(-d0);
        f1 = ex2(-d1);
        l0 *= f0;
        l1 *= f1;
        if (!boundary) {
          h0 *= f0;
          h1 *= f1;
        }
#pragma unroll
        for (int i = 0; i < lo; i++) S[i] *= (i & 2) ? f1 : f0;
      }
      if (lo > 0) shift(lo, d0, d1);
      e0 = d0;
      e1 = d1;
      m0 += d0;
      m1 += d1;
      shifted = true;
    };
    auto exps = [&](int lo, int hi) {
#pragma unroll
      for (int i = lo; i < hi; i += 4) {
        S[i] = ex2(S[i]);
        S[i + 1] = ex2(S[i + 1]);
        S[i + 2] = ex2(S[i + 2]);
        S[i + 3] = ex2(S[i + 3]);
        l0 += S[i] + S[i + 1];
        l1 += S[i + 2] + S[i + 3];
      }
    };
    auto to_p = [&]() {
#pragma unroll
      for (int j = 0; j < 32; j++) P[j] = pack_f16(S[2 * j], S[2 * j + 1]);
    };
    auto scale_o = [&](float f0, float f1) {
#pragma unroll
      for (int i = 0; i < 96; i += 4) {
        O[i] *= f0;
        O[i + 1] *= f0;
        O[i + 2] *= f1;
        O[i + 3] *= f1;
      }
    };
#pragma unroll
    for (int i = 0; i < 96; i++) asm volatile("" : "=f"(O[i]));
#pragma unroll
    for (int i = 0; i < 32; i++) asm volatile("" : "=r"(P[i]));
    if (threadIdx.x == 128) asm volatile("prefetch.tensormap [%0];" ::"l"(&tmo) : "memory");
    if (wg == 1) bar_arrive(1);
    int slot0 = 2;
#pragma unroll 1
    for (int s = 0;; s++) {
      const bool boundary = (s & 15) == 0;
      slot0 = slot0 >= 2 ? slot0 - 2 : slot0 + 3;
      if (boundary) mbar_wait(bars + kBarFullQ + 8 * wg, (s >> 4) & 1);
      mbar_wait(bars + kBarFullK01 + 8 * (s & 1), (s >> 1) & 1);
      bar_sync(1 + wg);
      pin(P);
      pin(O);
      wg_fence();
      issue_qk(s, slot0);
      mbar_wait(bars + kBarFullV + 8 * ((s - 1) & 1), ((s - 1) >> 1) & 1);
      wg_wait<1>();
      release(bars + kBarEmptyK0);
      if (s > 0) issue_pv(s - 1);
      else wg_commit();
      bar_arrive(2 - wg);
      wg_wait<1>();
      pin(S);
      release(bars + kBarEmptyK12 + 8 * (s & 1));
      if ((s & 15) == 15 && lane == 0) mbar_arrive_local(bars + kBarEmptyQ + 8 * wg);
      bool rescale = false;
      e0 = m0;
      e1 = m1;
#pragma unroll 1
      for (;;) {
        if (shifted) shift(0, e0, e1);
        if (rescale || !unsafe(0, kExpSplit, boundary)) break;
        use_true_max(0, boundary, boundary, sc0, sc1);
        rescale = true;
      }
      const bool late = unsafe(kExpSplit, 64, false);
      exps(0, kExpSplit);
      pin(S);
      asm volatile("st.volatile.shared.f32 [%0], %1;" ::"r"(bars + kDummy), "f"(l0 + l1) : "memory");
      wg_wait<0>();
      pin(O);
      pin(P);
      if (s > 0) {
        release(bars + kBarEmptyV + 8 * ((s - 1) & 1));
        if (((s + wg) & 15) == 0 && lane == 0) mbar_arrive_local(bars + kBarStage + 8 * (1 - wg));
      }
      if (late) {
        float f0, f1;
        use_true_max(kExpSplit, false, boundary, f0, f1);
        if (!boundary) {
          sc0 = f0;
          sc1 = f1;
          rescale = true;
        }
      }
      if (boundary && s > 0) {
        mbar_spin(bars + kBarStage + 8 * wg, ((s >> 4) - 1) & 1);
        stage_o(sbase + kSmemV + wg * kTileBytes + kTileBytes / 2, sc0, sc1, 0, 3);
        staged();
      } else if (rescale && s > 0) {
        scale_o(sc0, sc1);
      }
      pin(S);
      exps(kExpSplit, 64);
      to_p();
      if ((s & 15) == 7) {
        h0 = l0;
        h1 = l1;
      }
      if ((s & 15) == 15) {
        finish_l(s >> 4, sc0, sc1);
        m0 = m1 = l0 = l1 = 0.f;
        shifted = false;
      }
      if (s == own - 1) break;
    }
    uint32_t vw = pick(tail, kPlacesV<1>, kPlacesV<2>, kPlacesV<3>);
    uint32_t pw = wg ? pick(tail, kPlacesP<1, 1>, kPlacesP<2, 1>, kPlacesP<3, 1>)
                     : pick(tail, kPlacesP<1, 0>, kPlacesP<2, 0>, kPlacesP<3, 0>);
    auto next_v = [&]() {
      mbar_spin(bars + (vw >> 1 & 0x78), vw >> 2 & 1);
      const uint32_t vb = desc_lo(sbase, 1024) + (vw & 11) * 1024;
      vw >>= 8;
      return vb;
    };
    bool rescale = false;
    const float4* extra = (const float4*)(p.prob + (size_t)(blockIdx.x * kProbBytes + kProbExtra + (threadIdx.x >> 2) * 16));
    auto next_p = [&]() {
      mbar_spin(bars + (pw >> 1 & 0xF8), pw >> 3 & 1);
      const uint32_t a = sbase + (pw & 7) * 16384 + (threadIdx.x & 127) * 16;
      pw >>= 10;
      if (rescale) {
        const float4 b = __ldcg(extra);
        extra += 64;
        scale_p(a, ex2(b.x - m0), ex2(b.y - m1));
      }
      return a;
    };
    auto take = [&](uint32_t (&A)[32], uint32_t a) {
#pragma unroll
      for (int i = 0; i < 8; i++) {
        const uint4 x = lds128v(a + i * 2048);
        A[4 * i] = x.x, A[4 * i + 1] = x.y, A[4 * i + 2] = x.z, A[4 * i + 3] = x.w;
      }
      pin(A);
    };
    float f0 = 1.f, f1 = 1.f;
    uint32_t pa;
#pragma unroll 1
    for (int x = 0;; x++) {
      const uint32_t vb = next_v();
      bar_sync(1 + wg);
      pin(P);
      pin(O);
      wg_fence();
#pragma unroll
      for (int kk = 0; kk < 8; kk++)
        wgmma_rs_n192t(O, P[kk * 4], P[kk * 4 + 1], P[kk * 4 + 2], P[kk * 4 + 3], desc64<3072>(vb + kk * 384), 1);
      wg_commit();
      if (x < tail - 1) bar_arrive(2 - wg);
      if (x == 0) {
        mbar_spin(bars + kBarUnits, 1);
        const uint2 r = lds64(bars + kOffK + (threadIdx.x >> 2) * 8);
        float r0 = __uint_as_float(r.x), r1 = __uint_as_float(r.y);
        rescale = shifted || __any_sync(0xffffffffu, r0 < 0.f);
        if (rescale) {
          float n0 = m0, n1 = m1;
          r0 = r1 = 0.f;
#pragma unroll 1
          for (int j = 0;; j++) {
            const float4 b = __ldcg(extra + j * 64);
            const float x0 = fmaxf(n0, b.x), x1 = fmaxf(n1, b.y);
            r0 = r0 * ex2(n0 - x0) + b.z * ex2(b.x - x0);
            r1 = r1 * ex2(n1 - x1) + b.w * ex2(b.y - x1);
            n0 = x0;
            n1 = x1;
            if (j == tail - 1) break;
          }
          f0 = ex2(m0 - n0);
          f1 = ex2(m1 - n1);
          l0 *= f0;
          l1 *= f1;
          h0 *= f0;
          h1 *= f1;
          m0 = n0;
          m1 = n1;
        }
        l0 += r0;
        l1 += r1;
        finish_l(kWaves - 1, sc0, sc1);
        asm volatile("st.volatile.shared.f32 [%0], %1;" ::"r"(bars + kDummy), "f"(h0 + h1) : "memory");
      }
      pa = next_p();
      if (x == tail - 1) break;
      wg_wait<0>();
      pin(O);
      pin(P);
      if (rescale && x == 0) {
        scale_o(f0, f1);
        f0 = f1 = 1.f;
      }
      take(P, pa);
      release(bars + kBarEmptyV + 8 * ((own - 1 + x) & 1));
    }
    cluster_arrive();
    uint32_t R[32];
    take(R, pa);
    const uint32_t v_last = next_v();
    float T0[32], T1[32];
    auto tail_pv = [&](float (&T)[32], int c) {
      const uint32_t vb = v_last + c * 64;
      wg_fence();
#pragma unroll
      for (int kk = 0; kk < 8; kk++)
        wgmma_rs_n64t(T, R[kk * 4], R[kk * 4 + 1], R[kk * 4 + 2], R[kk * 4 + 3], desc64<3072>(vb + kk * 384), kk > 0);
      wg_commit();
    };
    uint32_t X[16];
    auto tail_pack = [&](float (&T)[32], int c) {
      pin(T);
#pragma unroll
      for (int i = 0; i < 16; i++) {
        const float f = (i & 1) ? sc1 : sc0;
        X[i] = pack_bf16(fmaf(T[2 * i], f, O[32 * c + 2 * i]), fmaf(T[2 * i + 1], f, O[32 * c + 2 * i + 1]));
      }
      pin(X);
    };
    auto tail_store = [&](int c) {
      const uint32_t addr = sbase + tail_stage + wg * (kTileBytes / 2) + c * 8192 +
                            ((warp & 3) * 16 + (lane & 15)) * 128 + (((lane >> 4) ^ (lane & 7)) << 4);
#pragma unroll
      for (int j = 0; j < 4; j++)
        asm volatile("stmatrix.sync.aligned.m8n8.x4.shared.b16 [%0], {%1, %2, %3, %4};" ::"r"(addr ^ (j * 32)), "r"(X[4 * j]),
                     "r"(X[4 * j + 1]), "r"(X[4 * j + 2]), "r"(X[4 * j + 3])
                     : "memory");
      __syncwarp();
      if (lane == 0) mbar_arrive_local(bars + kBarTail + 24 * wg + 8 * c);
    };
    tail_pv(T0, 0);
    f0 *= sc0;
    f1 *= sc1;
    wg_wait<1>();
    pin(P);
    auto prescale = [&](int c) {
      pin(O);
#pragma unroll
      for (int i = 32 * c; i < 32 * c + 32; i++) O[i] = (i & 2) ? fmaf(O[i], f1, h1) : fmaf(O[i], f0, h0);
      pin(O);
      mbar_spin(bars + kBarEmptyV + 8, 0);
    };
    prescale(0);
    tail_pv(T1, 1);
    if (wg == 0) bar_arrive(2);
    wg_wait<1>();
    tail_pack(T0, 0);
    tail_store(0);
    tail_pv(T0, 2);
    prescale(1);
    wg_wait<1>();
    tail_pack(T1, 1);
    tail_store(1);
    prescale(2);
    wg_wait<0>();
    tail_pack(T0, 2);
    tail_store(2);
    cluster_wait();
  }
}

}

extern "C" void kernel_launch(void* const* d_in, const int* in_sizes, int n_in, void* d_out, int out_size) {
  static CUtensorMap tmq, tmo;
  static const void *tm_q = nullptr, *tm_o = nullptr;
  static void *scratch, *flags, *prob;
  if (tm_q != d_in[0] || tm_o != d_out) {
    typedef CUresult (*EncodeFn)(CUtensorMap*, CUtensorMapDataType, cuuint32_t, void*, const cuuint64_t*,
                                 const cuuint64_t*, const cuuint32_t*, const cuuint32_t*, CUtensorMapInterleave,
                                 CUtensorMapSwizzle, CUtensorMapL2promotion, CUtensorMapFloatOOBfill);
    void* fn = nullptr;
    cudaDriverEntryPointQueryResult qr;
    cudaGetDriverEntryPoint("cuTensorMapEncodeTiled", &fn, cudaEnableDefault, &qr);
    cuuint64_t dims[2] = {(cuuint64_t)kD, (cuuint64_t)kH * kS};
    cuuint64_t strides[1] = {(cuuint64_t)kD * 2};
    cuuint32_t box[2] = {64, 64};
    cuuint32_t estr[2] = {1, 1};
    ((EncodeFn)fn)(&tmq, CU_TENSOR_MAP_DATA_TYPE_BFLOAT16, 2, d_in[0], dims, strides, box, estr,
                   CU_TENSOR_MAP_INTERLEAVE_NONE, CU_TENSOR_MAP_SWIZZLE_128B, CU_TENSOR_MAP_L2_PROMOTION_L2_128B,
                   CU_TENSOR_MAP_FLOAT_OOB_FILL_NONE);
    ((EncodeFn)fn)(&tmo, CU_TENSOR_MAP_DATA_TYPE_BFLOAT16, 2, d_out, dims, strides, box, estr,
                   CU_TENSOR_MAP_INTERLEAVE_NONE, CU_TENSOR_MAP_SWIZZLE_128B, CU_TENSOR_MAP_L2_PROMOTION_NONE,
                   CU_TENSOR_MAP_FLOAT_OOB_FILL_NONE);
    cudaFuncSetAttribute(attn_kernel, cudaFuncAttributeMaxDynamicSharedMemorySize, kSmemTotal);
    cudaGetSymbolAddress(&scratch, g_scratch);
    cudaGetSymbolAddress(&flags, g_flags);
    cudaGetSymbolAddress(&prob, g_prob);
    tm_q = d_in[0];
    tm_o = d_out;
  }
  Params p;
  p.q = (const __nv_bfloat16*)d_in[0];
  p.qk = (const int*)d_in[1];
  p.qv = (const int*)d_in[2];
  p.ks = (const __nv_bfloat16*)d_in[3];
  p.kz = (const __nv_bfloat16*)d_in[4];
  p.vs = (const __nv_bfloat16*)d_in[5];
  p.vz = (const __nv_bfloat16*)d_in[6];
  p.scratch = (uint8_t*)scratch;
  p.flags = (unsigned*)flags;
  p.prob = (uint8_t*)prob;
  attn_kernel<<<kOwners + kHelpers, 384, kSmemTotal>>>(p, tmq, tmo);
}
```

```cpp
#include <cuda_runtime.h>
#include <cuda_bf16.h>
#include <cuda.h>
#include <math.h>
#include <stdint.h>

namespace {

constexpr int kH = 32, kS = 2048, kD = 192;
constexpr int kGroupTok = 64;
constexpr int kBN = 128;
constexpr int kNBlk = kS / kBN;
constexpr int kWaves = 4;
constexpr int kSteps = kWaves * kNBlk;
constexpr int kTileBytes = kBN * kD * 2;
constexpr int kOwners = 128, kHelpers = 4;
constexpr uint32_t kTails = 0x33222112u;
constexpr uint32_t kJobs = 0x30214567u;
constexpr int kMaxTail = 3;
__device__ __forceinline__ int tail_blocks(int grp) { return (kTails >> (4 * grp)) & 3; }
constexpr uint32_t kHelperDelay = 42000, kHelperPrepare = 12000;
constexpr int kProbExtra = 512, kProbData = 4096, kProbBytes = kProbData + 2 * kMaxTail * 16384;
constexpr int kFlagTarget = 48;
constexpr int kFlagsPerGroup = kSteps;
constexpr float kLazyAbove = 15.f, kLazyBelow = 11.f;
constexpr int kLead = 3;
constexpr int kRing = 2 * kLead + 2;
static_assert((kRing & (kRing - 1)) == 0, "power of two");
constexpr int kBarPolls = 1 << 13, kFlagPolls = 1 << 16;

constexpr uint64_t pack_delays(int a, int b, int c, int d, int e, int f, int g, int h) {
  const int t[8] = {a, b, c, d, e, f, g, h};
  uint64_t w = 0;
  for (int i = 0; i < 8; i++) w |= (uint64_t)((t[i] + 16) / 32) << 8 * i;
  return w;
}
constexpr uint64_t kCodeDelays = pack_delays(500, 0, 0, 750, 1000, 1250, 1500, 1750), kQueryDelays = pack_delays(3340, 1900, 2600, 3860, 4380, 4900, 5420, 5940);
constexpr int kStatStep = 9;
static_assert(kStatStep + kLead < 15, "the first block of a head is expanded after its statistics have arrived");
constexpr uint32_t kOffsetFactor = 0x3EA03EA0u;
constexpr int kExpSplit = 32;
constexpr int kChunkBytes = kBN * 128;
constexpr int kSmemQ = 0;
constexpr int kSmemK = kTileBytes;
constexpr int kSmemV = kSmemK + 5 * kChunkBytes;
constexpr int kSmemBar = kSmemV + 2 * kTileBytes;
constexpr int kOffK = 256, kParV = kOffK + 2 * kD * 2, kBarBytes = kParV + 128;
constexpr int kSmemTotal = kSmemBar + kBarBytes + 1024;

constexpr int kBarFullK01 = 0, kBarFullV = 16, kBarEmptyK12 = 32, kBarEmptyV = 48, kBarFullQ = 64, kBarEmptyQ = 80,
              kBarFullK2 = 96, kBarEmptyK0 = 104, kBarStage = 112, kBarStaged = 128, kBarFullV2 = 144,
              kBarFullQ2 = 152, kBarCodes = 168, kBarTail = 176, kProgress = 224, kDummy = 228, kBarParams = 232,
              kBarUnits = 240;

constexpr uint32_t v_places(int n) {
  uint32_t w = (kSmemQ >> 14 | kBarFullQ << 1) << 8;
  for (int x = 0; x <= n; x += x ? 1 : 2) {
    const int v = kSteps - n + x - (x ? 2 : 1);
    w |= ((kSmemV + (v & 1) * kTileBytes) >> 14 | (v & 2) << 1 | (kBarFullV + 8 * (v & 1)) << 1) << 8 * x;
  }
  return w;
}
constexpr uint32_t p_places(int n, int wg) {
  constexpr int bar[6] = {kBarUnits, kBarUnits, kBarCodes, kBarParams, kBarFullQ + 8, kBarFullQ2};
  uint32_t w = 0;
  for (int j = 0; j < n; j++)
    w |= ((kSmemK >> 14) + (3 * (kSteps - n) + 2 * j + wg) % 5 | (j < 2) << 3 | bar[2 * j + wg] << 1) << 10 * j;
  return w;
}
template <int n> constexpr uint32_t kPlacesV = v_places(n);
template <int n, int wg> constexpr uint32_t kPlacesP = p_places(n, wg);
__device__ __forceinline__ uint32_t pick(int n, uint32_t a, uint32_t b, uint32_t c) { return n == 1 ? a : n == 2 ? b : c; }

__device__ __align__(1024) uint4 g_scratch[(size_t)8 * kRing * 2 * kTileBytes / 16];
constexpr int kFlagHelper = 8 * kFlagsPerGroup, kFlagStats = kFlagHelper + 8, kFlagDone = kFlagStats + 8;
__device__ __align__(16) unsigned g_flags[kFlagDone + 1];
constexpr int kHelperImages = kOwners * kProbBytes, kHeadStats = kHelperImages + 8 * kMaxTail * kTileBytes;
__device__ __align__(1024) uint4 g_prob[(kHeadStats + kH * 512) / 16];

__device__ __forceinline__ void wgmma_ss_n128(float (&d)[64], uint64_t da, uint64_t db, int scale_d) {
  asm volatile("{\n.reg .pred p;\nsetp.ne.b32 p, %66, 0;\n"
    "wgmma.mma_async.sync.aligned.m64n128k16.f32.bf16.bf16 "
    "{%0, %1, %2, %3, %4, %5, %6, %7, %8, %9, %10, %11, %12, %13, %14, %15, %16, %17, %18, %19, %20, %21, %22, %23, %24, %25, %26, %27, %28, %29, %30, %31, %32, %33, %34, %35, %36, %37, %38, %39, %40, %41, %42, %43, %44, %45, %46, %47, %48, %49, %50, %51, %52, %53, %54, %55, %56, %57, %58, %59, %60, %61, %62, %63}, %64, %65, p, 1, 1, 0, 0;\n}\n"
    : "+f"(d[0]), "+f"(d[1]), "+f"(d[2]), "+f"(d[3]), "+f"(d[4]), "+f"(d[5]), "+f"(d[6]), "+f"(d[7]), "+f"(d[8]), "+f"(d[9]), "+f"(d[10]), "+f"(d[11]), "+f"(d[12]), "+f"(d[13]), "+f"(d[14]), "+f"(d[15]), "+f"(d[16]), "+f"(d[17]), "+f"(d[18]), "+f"(d[19]), "+f"(d[20]), "+f"(d[21]), "+f"(d[22]), "+f"(d[23]), "+f"(d[24]), "+f"(d[25]), "+f"(d[26]), "+f"(d[27]), "+f"(d[28]), "+f"(d[29]), "+f"(d[30]), "+f"(d[31]), "+f"(d[32]), "+f"(d[33]), "+f"(d[34]), "+f"(d[35]), "+f"(d[36]), "+f"(d[37]), "+f"(d[38]), "+f"(d[39]), "+f"(d[40]), "+f"(d[41]), "+f"(d[42]), "+f"(d[43]), "+f"(d[44]), "+f"(d[45]), "+f"(d[46]), "+f"(d[47]), "+f"(d[48]), "+f"(d[49]), "+f"(d[50]), "+f"(d[51]), "+f"(d[52]), "+f"(d[53]), "+f"(d[54]), "+f"(d[55]), "+f"(d[56]), "+f"(d[57]), "+f"(d[58]), "+f"(d[59]), "+f"(d[60]), "+f"(d[61]), "+f"(d[62]), "+f"(d[63])
    : "l"(da), "l"(db), "r"(scale_d));
}
__device__ __forceinline__ void wgmma_new_n128(float (&d)[64], uint64_t da, uint64_t db) {
  asm volatile("{\n.reg .pred p;\nsetp.ne.b32 p, 0, 0;\n"
    "wgmma.mma_async.sync.aligned.m64n128k16.f32.bf16.bf16 "
    "{%0, %1, %2, %3, %4, %5, %6, %7, %8, %9, %10, %11, %12, %13, %14, %15, %16, %17, %18, %19, %20, %21, %22, %23, %24, %25, %26, %27, %28, %29, %30, %31, %32, %33, %34, %35, %36, %37, %38, %39, %40, %41, %42, %43, %44, %45, %46, %47, %48, %49, %50, %51, %52, %53, %54, %55, %56, %57, %58, %59, %60, %61, %62, %63}, %64, %65, p, 1, 1, 0, 0;\n}\n"
    : "=f"(d[0]), "=f"(d[1]), "=f"(d[2]), "=f"(d[3]), "=f"(d[4]), "=f"(d[5]), "=f"(d[6]), "=f"(d[7]), "=f"(d[8]), "=f"(d[9]), "=f"(d[10]), "=f"(d[11]), "=f"(d[12]), "=f"(d[13]), "=f"(d[14]), "=f"(d[15]), "=f"(d[16]), "=f"(d[17]), "=f"(d[18]), "=f"(d[19]), "=f"(d[20]), "=f"(d[21]), "=f"(d[22]), "=f"(d[23]), "=f"(d[24]), "=f"(d[25]), "=f"(d[26]), "=f"(d[27]), "=f"(d[28]), "=f"(d[29]), "=f"(d[30]), "=f"(d[31]), "=f"(d[32]), "=f"(d[33]), "=f"(d[34]), "=f"(d[35]), "=f"(d[36]), "=f"(d[37]), "=f"(d[38]), "=f"(d[39]), "=f"(d[40]), "=f"(d[41]), "=f"(d[42]), "=f"(d[43]), "=f"(d[44]), "=f"(d[45]), "=f"(d[46]), "=f"(d[47]), "=f"(d[48]), "=f"(d[49]), "=f"(d[50]), "=f"(d[51]), "=f"(d[52]), "=f"(d[53]), "=f"(d[54]), "=f"(d[55]), "=f"(d[56]), "=f"(d[57]), "=f"(d[58]), "=f"(d[59]), "=f"(d[60]), "=f"(d[61]), "=f"(d[62]), "=f"(d[63])
    : "l"(da), "l"(db));
}
__device__ __forceinline__ void wgmma_rs_n64t(float (&d)[32], uint32_t a0, uint32_t a1, uint32_t a2, uint32_t a3, uint64_t db, int scale_d) {
  asm volatile("{\n.reg .pred p;\nsetp.ne.b32 p, %37, 0;\n"
    "wgmma.mma_async.sync.aligned.m64n64k16.f32.f16.f16 "
    "{%0, %1, %2, %3, %4, %5, %6, %7, %8, %9, %10, %11, %12, %13, %14, %15, %16, %17, %18, %19, %20, %21, %22, %23, %24, %25, %26, %27, %28, %29, %30, %31}, {%32, %33, %34, %35}, %36, p, 1, 1, 1;\n}\n"
    : "+f"(d[0]), "+f"(d[1]), "+f"(d[2]), "+f"(d[3]), "+f"(d[4]), "+f"(d[5]), "+f"(d[6]), "+f"(d[7]), "+f"(d[8]), "+f"(d[9]), "+f"(d[10]), "+f"(d[11]), "+f"(d[12]), "+f"(d[13]), "+f"(d[14]), "+f"(d[15]), "+f"(d[16]), "+f"(d[17]), "+f"(d[18]), "+f"(d[19]), "+f"(d[20]), "+f"(d[21]), "+f"(d[22]), "+f"(d[23]), "+f"(d[24]), "+f"(d[25]), "+f"(d[26]), "+f"(d[27]), "+f"(d[28]), "+f"(d[29]), "+f"(d[30]), "+f"(d[31])
    : "r"(a0), "r"(a1), "r"(a2), "r"(a3), "l"(db), "r"(scale_d));
}
__device__ __forceinline__ void wgmma_rs_n192t(float (&d)[96], uint32_t a0, uint32_t a1, uint32_t a2, uint32_t a3, uint64_t db, int scale_d) {
  asm volatile("{\n.reg .pred p;\nsetp.ne.b32 p, %101, 0;\n"
    "wgmma.mma_async.sync.aligned.m64n192k16.f32.f16.f16 "
    "{%0, %1, %2, %3, %4, %5, %6, %7, %8, %9, %10, %11, %12, %13, %14, %15, %16, %17, %18, %19, %20, %21, %22, %23, %24, %25, %26, %27, %28, %29, %30, %31, %32, %33, %34, %35, %36, %37, %38, %39, %40, %41, %42, %43, %44, %45, %46, %47, %48, %49, %50, %51, %52, %53, %54, %55, %56, %57, %58, %59, %60, %61, %62, %63, %64, %65, %66, %67, %68, %69, %70, %71, %72, %73, %74, %75, %76, %77, %78, %79, %80, %81, %82, %83, %84, %85, %86, %87, %88, %89, %90, %91, %92, %93, %94, %95}, {%96, %97, %98, %99}, %100, p, 1, 1, 1;\n}\n"
    : "+f"(d[0]), "+f"(d[1]), "+f"(d[2]), "+f"(d[3]), "+f"(d[4]), "+f"(d[5]), "+f"(d[6]), "+f"(d[7]), "+f"(d[8]), "+f"(d[9]), "+f"(d[10]), "+f"(d[11]), "+f"(d[12]), "+f"(d[13]), "+f"(d[14]), "+f"(d[15]), "+f"(d[16]), "+f"(d[17]), "+f"(d[18]), "+f"(d[19]), "+f"(d[20]), "+f"(d[21]), "+f"(d[22]), "+f"(d[23]), "+f"(d[24]), "+f"(d[25]), "+f"(d[26]), "+f"(d[27]), "+f"(d[28]), "+f"(d[29]), "+f"(d[30]), "+f"(d[31]), "+f"(d[32]), "+f"(d[33]), "+f"(d[34]), "+f"(d[35]), "+f"(d[36]), "+f"(d[37]), "+f"(d[38]), "+f"(d[39]), "+f"(d[40]), "+f"(d[41]), "+f"(d[42]), "+f"(d[43]), "+f"(d[44]), "+f"(d[45]), "+f"(d[46]), "+f"(d[47]), "+f"(d[48]), "+f"(d[49]), "+f"(d[50]), "+f"(d[51]), "+f"(d[52]), "+f"(d[53]), "+f"(d[54]), "+f"(d[55]), "+f"(d[56]), "+f"(d[57]), "+f"(d[58]), "+f"(d[59]), "+f"(d[60]), "+f"(d[61]), "+f"(d[62]), "+f"(d[63]), "+f"(d[64]), "+f"(d[65]), "+f"(d[66]), "+f"(d[67]), "+f"(d[68]), "+f"(d[69]), "+f"(d[70]), "+f"(d[71]), "+f"(d[72]), "+f"(d[73]), "+f"(d[74]), "+f"(d[75]), "+f"(d[76]), "+f"(d[77]), "+f"(d[78]), "+f"(d[79]), "+f"(d[80]), "+f"(d[81]), "+f"(d[82]), "+f"(d[83]), "+f"(d[84]), "+f"(d[85]), "+f"(d[86]), "+f"(d[87]), "+f"(d[88]), "+f"(d[89]), "+f"(d[90]), "+f"(d[91]), "+f"(d[92]), "+f"(d[93]), "+f"(d[94]), "+f"(d[95])
    : "r"(a0), "r"(a1), "r"(a2), "r"(a3), "l"(db), "r"(scale_d));
}

__device__ __forceinline__ uint32_t desc_lo(uint32_t addr, uint32_t lbo) { return ((addr & 0x3FFFF) >> 4) | ((lbo >> 4) << 16); }
template <uint32_t SBO>
__device__ __forceinline__ uint64_t desc64(uint32_t lo) {
  uint64_t d;
  asm("mov.b64 %0, {%1, %2};" : "=l"(d) : "r"(lo), "n"((SBO >> 4) | (1u << 30)));
  return d;
}
__device__ __forceinline__ void wg_fence() { asm volatile("wgmma.fence.sync.aligned;" ::: "memory"); }
__device__ __forceinline__ void wg_commit() { asm volatile("wgmma.commit_group.sync.aligned;" ::: "memory"); }
template <int N>
__device__ __forceinline__ void wg_wait() { asm volatile("wgmma.wait_group.sync.aligned %0;" ::"n"(N) : "memory"); }
__device__ __forceinline__ void bar_sync(int id) { asm volatile("bar.sync %0, 256;" ::"r"(id) : "memory"); }
__device__ __forceinline__ void bar_arrive(int id) { asm volatile("bar.arrive %0, 256;" ::"r"(id) : "memory"); }

template <int N>
__device__ __forceinline__ void pin(float (&r)[N]) {
#pragma unroll
  for (int i = 0; i < N; i++) asm volatile("" : "+f"(r[i])::"memory");
}
template <int N>
__device__ __forceinline__ void pin(uint32_t (&r)[N]) {
#pragma unroll
  for (int i = 0; i < N; i++) asm volatile("" : "+r"(r[i])::"memory");
}

__device__ __forceinline__ void mbar_init(uint32_t bar, uint32_t count) {
  asm volatile("mbarrier.init.shared::cta.b64 [%0], %1;" ::"r"(bar), "r"(count) : "memory");
}
__device__ __forceinline__ void mbar_expect_tx(uint32_t bar, uint32_t bytes) {
  asm volatile("mbarrier.arrive.expect_tx.shared::cta.b64 _, [%0], %1;" ::"r"(bar), "r"(bytes) : "memory");
}
__device__ __forceinline__ void mbar_arrive_local(uint32_t bar) {
  asm volatile("mbarrier.arrive.shared::cta.b64 _, [%0];" ::"r"(bar) : "memory");
}
__device__ __forceinline__ void mbar_arrive_cluster(uint32_t bar, uint32_t cta) {
  asm volatile(
      "{\n.reg .b32 ra;\nmapa.shared::cluster.u32 ra, %0, %1;\n"
      "mbarrier.arrive.shared::cluster.b64 _, [ra];\n}" ::"r"(bar),
      "r"(cta)
      : "memory");
}
__device__ __forceinline__ bool mbar_try(uint32_t bar, uint32_t parity) {
  uint32_t ok;
  asm volatile(
      "{\n.reg .pred p;\nmbarrier.try_wait.parity.shared::cta.b64 p, [%1], %2;\nselp.u32 %0, 1, 0, p;\n}"
      : "=r"(ok)
      : "r"(bar), "r"(parity)
      : "memory");
  return ok;
}
__device__ __forceinline__ uint32_t now_clk() {
  uint32_t t;
  asm volatile("mov.u32 %0, %%clock;" : "=r"(t));
  return t;
}
__device__ __forceinline__ void mbar_wait(uint32_t bar, uint32_t parity) {
  if (mbar_try(bar, parity)) return;
#pragma unroll 1
  for (int n = now_clk() & 1; n < kBarPolls; n++)
    if (mbar_try(bar, parity)) break;
}
__device__ __forceinline__ void mbar_spin(uint32_t bar, uint32_t parity) {
#pragma unroll 1
  for (int n = 0; n < kBarPolls; n++)
    if (mbar_try(bar, parity)) break;
}
__device__ __forceinline__ bool elect_one() {
  uint32_t r;
  asm volatile("{\n.reg .pred p;\nelect.sync _|p, 0xffffffff;\nselp.u32 %0, 1, 0, p;\n}" : "=r"(r));
  return r;
}
__device__ __forceinline__ void bulk_load(uint32_t dst, const void* src, uint32_t bytes, uint32_t bar) {
  asm volatile("cp.async.bulk.shared::cluster.global.mbarrier::complete_tx::bytes [%0], [%1], %2, [%3];" ::"r"(dst),
               "l"(src), "r"(bytes), "r"(bar)
               : "memory");
}
__device__ __forceinline__ void bulk_copy_peer(uint32_t addr, uint32_t bytes, uint32_t bar, uint32_t cta) {
  asm volatile(
      "{\n.reg .b32 ra, rb;\nmapa.shared::cluster.u32 ra, %0, %3;\nmapa.shared::cluster.u32 rb, %2, %3;\n"
      "cp.async.bulk.shared::cluster.shared::cta.mbarrier::complete_tx::bytes [ra], [%0], %1, [rb];\n}" ::"r"(addr),
      "r"(bytes), "r"(bar), "r"(cta)
      : "memory");
}
__device__ __forceinline__ void bulk_load_mc(uint32_t dst, const void* src, uint32_t bytes, uint32_t bar) {
  asm volatile(
      "cp.async.bulk.shared::cluster.global.mbarrier::complete_tx::bytes.multicast::cluster [%0], [%1], %2, [%3], "
      "%4;" ::"r"(dst),
      "l"(src), "r"(bytes), "r"(bar), "h"((uint16_t)3)
      : "memory");
}
constexpr uint64_t kEvictFirst = 0x12F0000000000000ull;
__device__ __forceinline__ void tma_load_2d(uint32_t dst, const CUtensorMap* map, int c0, int c1, uint32_t bar) {
  asm volatile(
      "cp.async.bulk.tensor.2d.shared::cluster.global.mbarrier::complete_tx::bytes.L2::cache_hint [%0], [%1, {%3, %4}], "
      "[%2], %5;" ::"r"(dst),
      "l"(map), "r"(bar), "r"(c0), "r"(c1), "l"(kEvictFirst)
      : "memory");
}
__device__ __forceinline__ void tma_store_2d(const CUtensorMap* map, uint32_t src, int c0, int c1) {
  asm volatile("cp.async.bulk.tensor.2d.global.shared::cta.bulk_group [%0, {%2, %3}], [%1];" ::"l"(map), "r"(src),
               "r"(c0), "r"(c1)
               : "memory");
}
__device__ __forceinline__ void cluster_arrive() { asm volatile("barrier.cluster.arrive.relaxed;" ::: "memory"); }
__device__ __forceinline__ void cluster_wait() { asm volatile("barrier.cluster.wait;" ::: "memory"); }
__device__ __forceinline__ float ex2(float x) {
  float y;
  asm("ex2.approx.ftz.f32 %0, %1;" : "=f"(y) : "f"(x));
  return y;
}
__device__ __forceinline__ float rcp(float x) {
  float y;
  asm("rcp.approx.ftz.f32 %0, %1;" : "=f"(y) : "f"(x));
  return y;
}
__device__ __forceinline__ uint32_t pack_bf16(float lo, float hi) {
  uint32_t r;
  asm("cvt.rn.bf16x2.f32 %0, %1, %2;" : "=r"(r) : "f"(hi), "f"(lo));
  return r;
}

__device__ __forceinline__ uint32_t pack_f16(float lo, float hi) {
  uint32_t r;
  asm("cvt.rn.f16x2.f32 %0, %1, %2;" : "=r"(r) : "f"(hi), "f"(lo));
  return r;
}

__device__ __forceinline__ uint32_t scale_f16(uint32_t w, float f) {
  float x, y;
  asm("{\n.reg .b16 a, b;\nmov.b32 {a, b}, %2;\ncvt.f32.f16 %0, a;\ncvt.f32.f16 %1, b;\n}" : "=f"(x), "=f"(y) : "r"(w));
  return pack_f16(x * f, y * f);
}

struct Params {
  const int* qk;
  const int* qv;
  const __nv_bfloat16* ks;
  const __nv_bfloat16* kz;
  const __nv_bfloat16* vs;
  const __nv_bfloat16* vz;
  const __nv_bfloat16* q;
  uint8_t* scratch;
  unsigned* flags;
  uint8_t* prob;
};

__device__ __forceinline__ int unit_row(int step, int grp, int mt) {
  return ((step >> 4) * 8 + grp) * kS + (step & 15) * kBN + mt * 8;
}
__device__ __forceinline__ uint8_t* tile_image(const Params& p, int step, int grp, int is_v) {
  return p.scratch + ((size_t)(grp * kRing + (unsigned)step % kRing) * 2 + is_v) * kTileBytes;
}
struct Unit { uint4 x[4]; uint2 s, z; };

__device__ __forceinline__ uint4 ldg128(const void* a) {
  uint4 v;
  asm volatile("ld.global.nc.L1::no_allocate.v4.u32 {%0, %1, %2, %3}, [%4];"
               : "=r"(v.x), "=r"(v.y), "=r"(v.z), "=r"(v.w)
               : "l"(a)
               : "memory");
  return v;
}
__device__ __forceinline__ uint4 ldg128_last_use(const void* a) {
  uint4 v;
  asm volatile("ld.global.nc.L1::no_allocate.L2::cache_hint.v4.u32 {%0, %1, %2, %3}, [%4], %5;"
               : "=r"(v.x), "=r"(v.y), "=r"(v.z), "=r"(v.w)
               : "l"(a), "l"(kEvictFirst)
               : "memory");
  return v;
}
__device__ __forceinline__ uint2 ldg64(const void* a) {
  uint2 v;
  asm volatile("ld.global.nc.L1::no_allocate.v2.u32 {%0, %1}, [%2];" : "=r"(v.x), "=r"(v.y) : "l"(a));
  return v;
}
__device__ __forceinline__ void stg64(uint64_t a, uint32_t x, uint32_t y) {
  asm volatile("st.global.L1::no_allocate.v2.u32 [%0], {%1, %2};" ::"l"(a), "r"(x), "r"(y) : "memory");
}
__device__ __forceinline__ uint32_t bf2_mul(uint32_t a, uint32_t b) {
  uint32_t r;
  asm("mul.rn.bf16x2 %0, %1, %2;" : "=r"(r) : "r"(a), "r"(b));
  return r;
}
__device__ __forceinline__ uint32_t bf2_fma(uint32_t a, uint32_t b, uint32_t c) {
  uint32_t r;
  asm("fma.rn.bf16x2 %0, %1, %2, %3;" : "=r"(r) : "r"(a), "r"(b), "r"(c));
  return r;
}
__device__ __forceinline__ uint32_t h2_fma(uint32_t a, uint32_t b, uint32_t c) {
  uint32_t r;
  asm("fma.rn.f16x2 %0, %1, %2, %3;" : "=r"(r) : "r"(a), "r"(b), "r"(c));
  return r;
}
__device__ __forceinline__ uint32_t h2_mul(uint32_t a, uint32_t b) {
  uint32_t r;
  asm("mul.rn.f16x2 %0, %1, %2;" : "=r"(r) : "r"(a), "r"(b));
  return r;
}
__device__ __forceinline__ float bf_lo(uint32_t w) { return __uint_as_float(w << 16); }
__device__ __forceinline__ float bf_hi(uint32_t w) { return __uint_as_float(w & 0xffff0000u); }
__device__ __forceinline__ uint32_t codes_bf16(uint32_t a, uint32_t b) { return pack_bf16((float)(int)a, (float)(int)b); }
__device__ __forceinline__ uint2 lds64(uint32_t a) {
  uint2 v;
  asm volatile("ld.shared.v2.u32 {%0, %1}, [%2];" : "=r"(v.x), "=r"(v.y) : "r"(a));
  return v;
}
__device__ __forceinline__ uint4 lds128(uint32_t a) {
  uint4 v;
  asm volatile("ld.shared.v4.u32 {%0, %1, %2, %3}, [%4];" : "=r"(v.x), "=r"(v.y), "=r"(v.z), "=r"(v.w) : "r"(a));
  return v;
}
__device__ __forceinline__ uint4 lds128v(uint32_t a) {
  uint4 v;
  asm volatile("ld.shared.v4.u32 {%0, %1, %2, %3}, [%4];" : "=r"(v.x), "=r"(v.y), "=r"(v.z), "=r"(v.w) : "r"(a) : "memory");
  return v;
}
__device__ __forceinline__ void scale_p(uint32_t a, float f0, float f1) {
#pragma unroll 1
  for (int i = 0; i < 16; i++, a += i & 1 ? 8 : 2040) {
    const uint2 x = lds64(a);
    asm volatile("st.shared.v2.u32 [%0], {%1, %2};" ::"r"(a), "r"(scale_f16(x.x, f0)), "r"(scale_f16(x.y, f1)) : "memory");
  }
}
__device__ __forceinline__ uint32_t k_scale(uint32_t s) { return bf2_fma(s, 0x40D540D5u, bf2_mul(s, 0x3BEE3BEEu)); }
__device__ __forceinline__ uint32_t k_zero(uint32_t z) { return bf2_mul(z, 0xBC80BC80u); }
__device__ __forceinline__ uint32_t k_pair(uint32_t x, uint32_t xs, uint32_t z, uint32_t s, uint32_t off) {
  return bf2_fma(bf2_fma(x, xs, z), s, off);
}
constexpr uint32_t kByteScaleK = 0x7F007F00u, kBf16ScaleK = 0x3C803C80u, kByteScaleV = 0x60006000u;
template <bool kIsV>
__device__ __forceinline__ void load_unit(const Params& p, int row0, uint32_t t, Unit& d) {
  const uint32_t hi = t >= 48 ? 1 : 0, q = t - hi * 48;
  const uint8_t* src = (const uint8_t*)((kIsV ? p.qv : p.qk) + (size_t)row0 * kD) + (hi * 3072 + q * 16);
#pragma unroll
  for (int i = 0; i < 4; i++) d.x[i] = ldg128_last_use(src + i * 768);
  if (kIsV) {
    uint32_t o = hi * 8;
    asm("" : "+r"(o));
    d.s = ldg64((const uint8_t*)(p.vs + row0) + o);
    d.z = ldg64((const uint8_t*)(p.vz + row0) + o);
  } else {
    d.s = ldg64((const uint8_t*)(p.ks + (row0 / kGroupTok) * kD) + q * 8);
    d.z = ldg64((const uint8_t*)(p.kz + (row0 / kGroupTok) * kD) + q * 8);
  }
}
__device__ __forceinline__ bool codes_are_bytes(const Unit& d, uint32_t a = 0) {
#pragma unroll
  for (int i = 0; i < 4; i++) a |= d.x[i].x | d.x[i].y | d.x[i].z | d.x[i].w;
  return !__any_sync(0xffffffffu, a > 255);
}
template <int kHalf>
__device__ __forceinline__ uint32_t dup16(uint32_t w) {
  uint32_t v;
  if (kHalf == 0) asm("{\n.reg .b16 a, b;\nmov.b32 {a, b}, %1;\nmov.b32 %0, {a, a};\n}" : "=r"(v) : "r"(w));
  else asm("{\n.reg .b16 a, b;\nmov.b32 {a, b}, %1;\nmov.b32 %0, {b, b};\n}" : "=r"(v) : "r"(w));
  return v;
}
template <bool kIsV>
__device__ __forceinline__ uint64_t unit_dst(const Params& p, int step, int grp, int mt, uint32_t t, int own = kSteps) {
  const uint32_t hi = t >= 48 ? 1 : 0, q = t - hi * 48;
  return (uint64_t)(tile_image(p, step, grp, kIsV && step < own) + mt * (kIsV ? 3072 : 1024)) +
         ((q >> 4) * (kIsV ? 1024 : kChunkBytes) + hi * 512 + (q & 1) * 8 + ((((q & 15) >> 1) ^ (hi * 4)) << 4));
}
__device__ __forceinline__ void store_k(uint64_t dst, int slot, uint32_t t, const Unit& d, uint32_t bars, bool bytes) {
  const uint2 off = lds64(bars + kOffK + slot * (kD * 2) + (t >= 48 ? t - 48 : t) * 8);
  uint32_t x[8];
  if (bytes) {
#pragma unroll
    for (int i = 0; i < 4; i++) {
      x[2 * i] = d.x[i].y * 65536u + d.x[i].x;
      x[2 * i + 1] = d.x[i].w * 65536u + d.x[i].z;
    }
  } else {
#pragma unroll
    for (int i = 0; i < 4; i++) {
      x[2 * i] = codes_bf16(d.x[i].x, d.x[i].y);
      x[2 * i + 1] = codes_bf16(d.x[i].z, d.x[i].w);
    }
  }
  const uint32_t xs = bytes ? kByteScaleK : kBf16ScaleK;
  const uint32_t s0 = k_scale(d.s.x), s1 = k_scale(d.s.y), z0 = k_zero(d.z.x), z1 = k_zero(d.z.y);
#pragma unroll
  for (int i = 0; i < 4; i++)
    stg64((dst ^ (i * 16)) + i * 128, k_pair(x[2 * i], xs, z0, s0, off.x), k_pair(x[2 * i + 1], xs, z1, s1, off.y));
}
constexpr uint32_t kCentreBits = 256 * 0x10001u;
constexpr float kCentre = 256 * (1.f / 16777216);
__device__ __forceinline__ void store_v(uint64_t dst, int step, const Unit& d, uint32_t bars) {
  const uint2 par = lds64(bars + kParV + (step >> 4) * 32);
  const float alpha = __uint_as_float(par.x), centre = __uint_as_float(par.y ^ (step & 8) << 28);
#pragma unroll
  for (int i = 0; i < 4; i++) {
    const uint32_t zw = i < 2 ? d.z.x : d.z.y, sw = i < 2 ? d.s.x : d.s.y;
    const uint32_t zz = (i & 1) ? dup16<1>(zw) : dup16<0>(zw), ss = (i & 1) ? dup16<1>(sw) : dup16<0>(sw);
    auto pair = [&](uint32_t a, uint32_t b) {
      uint32_t v;
      asm("{\n.reg .b32 t;\nsub.rn.bf16x2 t, %1, %2;\nmul.rn.bf16x2 %0, t, %3;\n}"
          : "=r"(v)
          : "r"(codes_bf16(a, b)), "r"(zz), "r"(ss));
      return pack_f16(fmaf(bf_lo(v), alpha, centre), fmaf(bf_hi(v), alpha, centre));
    };
    stg64((dst ^ (i * 16)) + i * 128, pair(d.x[i].x, d.x[i].y), pair(d.x[i].z, d.x[i].w));
  }
}
__device__ __forceinline__ void store_v_any(uint64_t dst, int step, const Unit& d, uint32_t bars) {
  const uint2 par = lds64(bars + kParV + (step >> 4) * 32 + 16);
  const uint32_t z0 = d.z.x - 0x40004000u, z1 = d.z.y - 0x40004000u;
  if (!codes_are_bytes(d, ((z0 | z1) & 0xFC00FC00u) | ((d.s.x | d.s.y) & 0x80008000u)) || par.x == 0) {
    store_v(dst, step, d, bars);
    return;
  }
  const uint2 z = make_uint2(z0 * 8 + 0x84008400u, z1 * 8 + 0x84008400u);
  const uint2 s = make_uint2(h2_mul(d.s.x * 8 + par.y, par.x), h2_mul(d.s.y * 8 + par.y, par.x));
  const uint32_t c2 = kCentreBits ^ (step & 8) * 0x10001000u;
#pragma unroll
  for (int i = 0; i < 4; i++) {
    const uint32_t zw = i < 2 ? z.x : z.y, sw = i < 2 ? s.x : s.y;
    const uint32_t zz = (i & 1) ? dup16<1>(zw) : dup16<0>(zw), ss = (i & 1) ? dup16<1>(sw) : dup16<0>(sw);
    stg64((dst ^ (i * 16)) + i * 128, h2_fma(h2_fma(d.x[i].y * 65536u + d.x[i].x, kByteScaleV, zz), ss, c2),
          h2_fma(h2_fma(d.x[i].w * 65536u + d.x[i].z, kByteScaleV, zz), ss, c2));
  }
}
struct Stat { uint4 s[4], z[4]; };
struct Range { uint4 lo; uint32_t hi; };
__device__ __forceinline__ void stat_load(const Params& p, int head, int j, uint32_t lane, Stat& d) {
  const bool v = lane >= 24;
  const uint32_t off = v ? (head * kS + j * 256) * 2 + (lane - 24) * 16 : (head * 32 + j * 4) * (kD * 2) + lane * 16;
  const uint32_t step = v ? 128 : kD * 2;
  const uint8_t *ps = (const uint8_t*)(v ? p.vs : p.ks), *pz = (const uint8_t*)(v ? p.vz : p.kz);
#pragma unroll
  for (int i = 0; i < 4; i++) {
    uint32_t o = off + i * step;
    asm("" : "+r"(o));
    d.s[i] = ldg128(ps + o);
    d.z[i] = ldg128(pz + o);
  }
}
__device__ __forceinline__ uint32_t range2(uint32_t s, uint32_t z) {
  uint32_t r;
  asm("{\n.reg .b32 m;\nmax.xorsign.abs.bf16x2 m, %2, %3;\nmul.rn.bf16x2 %0, %1, m;\n}"
      : "=r"(r)
      : "r"(s), "r"(z), "r"(0x3F803F80u));
  return r & 0x7fff7fffu;
}
__device__ __forceinline__ void stat_add(const Stat& d, Range& r) {
  auto col = [&](uint32_t& lo, uint32_t a, uint32_t b, uint32_t c, uint32_t e) {
    lo = __vimin3_u16x2(__vimin3_u16x2(lo, a, b), c, e);
    r.hi = __vimax3_u16x2(__vimax3_u16x2(r.hi, a, b), c, e);
  };
  col(r.lo.x, range2(d.s[0].x, d.z[0].x), range2(d.s[1].x, d.z[1].x), range2(d.s[2].x, d.z[2].x), range2(d.s[3].x, d.z[3].x));
  col(r.lo.y, range2(d.s[0].y, d.z[0].y), range2(d.s[1].y, d.z[1].y), range2(d.s[2].y, d.z[2].y), range2(d.s[3].y, d.z[3].y));
  col(r.lo.z, range2(d.s[0].z, d.z[0].z), range2(d.s[1].z, d.z[1].z), range2(d.s[2].z, d.z[2].z), range2(d.s[3].z, d.z[3].z));
  col(r.lo.w, range2(d.s[0].w, d.z[0].w), range2(d.s[1].w, d.z[1].w), range2(d.s[2].w, d.z[2].w), range2(d.s[3].w, d.z[3].w));
}
__device__ __forceinline__ void sts128(uint32_t a, uint32_t x, uint32_t y, uint32_t z, uint32_t w) {
  asm volatile("st.shared.v4.u32 [%0], {%1, %2, %3, %4};" ::"r"(a), "r"(x), "r"(y), "r"(z), "r"(w) : "memory");
}
__device__ __forceinline__ uint4 stat_finish(const Range& r, uint32_t lane) {
  const bool v = lane >= 24;
  const uint32_t lo = __vimin3_u16x2(__vminu2(r.lo.x, r.lo.y), r.lo.z, r.lo.w);
  const float amin = bf_hi(__reduce_min_sync(0xffffffffu, v ? min(lo, lo << 16) : ~0u));
  const float amax = fmaxf(bf_hi(__reduce_max_sync(0xffffffffu, v ? max(r.hi, r.hi << 16) : 0u)), 1e-30f);
  const bool centred = amax <= 2.f * amin && amax <= 1e30f;
  const uint32_t a15 = __float_as_uint(__fdividef(centred ? 0.98f * kCentre * 32768 : 16.f * 32768, amax)) & 0xFFFFE000u;
  const float alpha = __uint_as_float(a15) * (1.f / 32768);
  if (lane == 24)
    return make_uint4(__float_as_uint(alpha), centred ? __float_as_uint(kCentre) : 0u, __float_as_uint(__fdividef(1.f, alpha)), 0u);
  if (v) return make_uint4(centred ? (0x3C00u | (a15 >> 13 & 0x3FFu)) * 0x10001u : 0u, ((a15 >> 23) - 239u) * 0x4000400u, 0u, 0u);
  return make_uint4(bf2_mul(r.lo.x, kOffsetFactor), bf2_mul(r.lo.y, kOffsetFactor), bf2_mul(r.lo.z, kOffsetFactor),
                    bf2_mul(r.lo.w, kOffsetFactor));
}
__device__ __forceinline__ void stat_keep(const uint4& x, int wave, uint32_t lane, uint32_t bars) {
  if (lane < 26)
    sts128(bars + lane * 16 + (lane < 24 ? kOffK + (wave & 1) * (kD * 2) : kParV - 24 * 16 + wave * 32), x.x, x.y, x.z, x.w);
}
__device__ __forceinline__ void prefetch_bulk(const void* g, uint32_t bytes) {
  asm volatile("cp.async.bulk.prefetch.L2.global [%0], %1;" ::"l"(g), "r"(bytes) : "memory");
}
__device__ __forceinline__ void publish(const Params& p, int flag, int grp) {
  __syncwarp();
  asm volatile(
      "{\n.reg .pred p;\nelect.sync _|p, 0xffffffff;\n@p red.release.gpu.global.add.u32 [%0], 1;\n}" ::"l"(
          p.flags + grp * kFlagsPerGroup + flag)
      : "memory");
}
__device__ __forceinline__ void flag_wait(const unsigned* f) {
#pragma unroll 1
  for (int n = 0; n < kFlagPolls; n++) {
    unsigned v;
    asm volatile("ld.acquire.gpu.global.u32 %0, [%1];" : "=r"(v) : "l"(f) : "memory");
    if (__all_sync(0xffffffffu, v >= kFlagTarget)) break;
  }
  asm volatile("fence.proxy.async.global;" ::: "memory");
}

__device__ __forceinline__ void helper_cta(const Params& p, const CUtensorMap& tmq, uint32_t sbase, uint32_t t_start) {
  constexpr int kFullQ = 0, kEmptyQ = 32, kDone = 64, kFullK = 72;
  const uint32_t bars = sbase + kSmemBar, sq = sbase + kMaxTail * kTileBytes;
  const int warp = __shfl_sync(0xffffffffu, threadIdx.x >> 5, 0);
  const int lane = threadIdx.x & 31;
  const int grp0 = blockIdx.x - kOwners;
  auto job_grp = [&](int n) { return (int)(kJobs >> (16 * n + 4 * grp0) & 7); };
  auto job_row = [&](int n) { return ((kWaves - 1) * 8 + job_grp(n)) * kS; };
  auto job_images = [&](int n) { return p.prob + (size_t)(kHelperImages + job_grp(n) * (kMaxTail * kTileBytes)); };
  if (threadIdx.x == 0) {
    for (int i = 0; i < 3; i++) {
      mbar_init(bars + kFullQ + 8 * i, 1);
      mbar_init(bars + kEmptyQ + 8 * i, 4);
    }
    mbar_init(bars + kDone, 8);
    mbar_init(bars + kFullK, 1);
    asm volatile("fence.proxy.async.shared::cta;" ::: "memory");
  }
  auto sleep_until = [&](uint32_t t) {
    while (now_clk() - t_start < t) __nanosleep(200);
  };
  auto wait_long = [&](uint32_t bar, uint32_t parity) {
#pragma unroll 1
    for (int k = 0; k < kFlagPolls && !mbar_try(bar, parity); k++) __nanosleep(200);
  };
  sleep_until(kHelperPrepare);
  if (warp < 6) {
    const int head = job_row(warp & 1) / kS - (warp >> 1) * 8, blocks = tail_blocks(head & 7);
    if (warp < 2 && elect_one()) prefetch_bulk(p.qk + (size_t)(head * kS + kS - blocks * kBN) * kD, blocks * 2 * kTileBytes);
    __syncwarp();
    Range r = {make_uint4(~0u, ~0u, ~0u, ~0u), 0u};
#pragma unroll 1
    for (int j = 0; j < 8; j += 2) {
      Stat a, b;
      stat_load(p, head, j, lane, a);
      stat_load(p, head, j + 1, lane, b);
      stat_add(a, r);
      stat_add(b, r);
    }
    const uint4 x = stat_finish(r, lane);
    if (warp < 2) stat_keep(x, warp, lane, bars);
    *(uint4*)(p.prob + kHeadStats + head * 512 + lane * 16) = x;
  }
  __syncthreads();
  if (threadIdx.x < 2)
    asm volatile("red.release.gpu.global.add.u32 [%0], %1;" ::"l"(p.flags + kFlagStats + job_grp(threadIdx.x)), "n"(kFlagTarget)
                 : "memory");
#pragma unroll 1
  for (int n = 0; n < 2; n++) {
    const int team = warp / 3, units = 16 * tail_blocks(job_grp(n));
    const uint32_t t = threadIdx.x - team * 96, hi = t >= 48 ? 1 : 0, q = t - hi * 48;
    const int row = job_row(n) + kS - units * 8;
    const uint64_t dst = (uint64_t)job_images(n) +
                         ((q >> 4) * kChunkBytes + hi * 512 + (q & 1) * 8 + ((((q & 15) >> 1) ^ (hi * 4)) << 4));
    auto unit_at = [&](int m) { return (m >> 4) * kTileBytes + (m & 15) * 1024; };
#pragma unroll 1
    for (int m = 4 * team; m < units; m += 16) {
      Unit u[4];
#pragma unroll
      for (int i = 0; i < 4; i++) load_unit<false>(p, row + (m + i) * 8, t, u[i]);
#pragma unroll
      for (int i = 0; i < 4; i++) store_k(dst + unit_at(m + i), n, t, u[i], bars, codes_are_bytes(u[i]));
    }
  }
  __threadfence();
  __syncthreads();
  if (warp >= 8) {
    asm volatile("setmaxnreg.dec.sync.aligned.u32 104;");
    if (warp == 8) {
      sleep_until(kHelperDelay);
      uint32_t slot = 0, parity = 1;
#pragma unroll 1
      for (int z = 0; z < 64; z++) {
        const int n = z >> 5, blocks = tail_blocks(job_grp(n));
        if (z == 0 || z == 35) {
          if (n) mbar_spin(bars + kDone, 0);
          asm volatile("fence.proxy.async.global;" ::: "memory");
          if (elect_one()) {
            mbar_expect_tx(bars + kFullK, blocks * kTileBytes);
            bulk_load(sbase, job_images(n), blocks * kTileBytes, bars + kFullK);
          }
          __syncwarp();
        }
        const int half = blocks == 1 ? (z & 28) + (z & 1) * 2 + ((z >> 1) & 1) : z & 31;
        const uint32_t bar = bars + kFullQ + 8 * slot;
        mbar_spin(bars + kEmptyQ + 8 * slot, parity);
        if (elect_one()) {
          mbar_expect_tx(bar, kTileBytes / 2);
#pragma unroll
          for (int c = 0; c < 3; c++)
            tma_load_2d(sq + slot * (kTileBytes / 2) + c * 8192, &tmq, c * 64, job_row(n) + half * 64, bar);
          const int v = min(z + 2 * 3, 63);
          prefetch_bulk(p.q + (size_t)(job_row(v >> 5) + (v & 31) * 64) * kD, kTileBytes / 2);
          if (z == 24) prefetch_bulk(job_images(1), tail_blocks(job_grp(1)) * kTileBytes);
        }
        __syncwarp();
        if (++slot == 3) {
          slot = 0;
          parity ^= 1;
        }
      }
    } else if (warp == 9) {
#pragma unroll 1
      for (int n = 0; n < 2; n++) {
        wait_long(bars + kDone, n);
        if (elect_one()) {
          asm volatile("red.release.gpu.global.add.u32 [%0], %1;" ::"l"(p.flags + kFlagHelper + job_grp(n)), "n"(kFlagTarget)
                       : "memory");
        }
        __syncwarp();
      }
    }
    return;
  }
  asm volatile("setmaxnreg.inc.sync.aligned.u32 200;");
  const int wg = warp >> 2;
  float A[64], B[64];
#pragma unroll
  for (int i = 0; i < 64; i++) asm volatile("" : "=f"(A[i]), "=f"(B[i]));
  int n, blocks;
  auto issue = [&](float (&S)[64], int tile, int j) {
    const uint32_t z = 32 * n + (blocks == 1 ? (tile >> 1) * 4 + 2 * wg + (tile & 1) : 2 * tile + wg);
    const uint32_t turn = z * 43 >> 7, slot = z - 3 * turn;
    if (j == 0) mbar_wait(bars + kFullQ + 8 * slot, turn & 1);
    const uint32_t kb = desc_lo(sbase, 16) + j * (kTileBytes >> 4);
    const uint32_t qb = desc_lo(sq, 16) + slot * (kTileBytes >> 5);
    bar_sync(2 + wg);
    wg_fence();
    wgmma_new_n128(S, desc64<1024>(qb), desc64<1024>(kb));
#pragma unroll
    for (int kk = 1; kk < 12; kk++)
      wgmma_ss_n128(S, desc64<1024>(qb + (kk >> 2) * 512 + (kk & 3) * 2), desc64<1024>(kb + (kk >> 2) * 1024 + (kk & 3) * 2), 1);
    wg_commit();
    bar_arrive(3 - wg);
    return bars + kEmptyQ + 8 * slot;
  };
  float r0, r1;
  auto finish = [&](float (&S)[64], int tile, int j) {
    pin(S);
    int a0 = 0, a1 = 0;
    uint32_t u0 = ~0u, u1 = ~0u;
#pragma unroll
    for (int i = 0; i < 64; i += 4) {
      a0 = __vimax3_s32(a0, __float_as_int(S[i]), __float_as_int(S[i + 1]));
      a1 = __vimax3_s32(a1, __float_as_int(S[i + 2]), __float_as_int(S[i + 3]));
      if (i < 16) {
        u0 = __vimin3_u32(u0, __float_as_uint(S[i]), __float_as_uint(S[i + 1]));
        u1 = __vimin3_u32(u1, __float_as_uint(S[i + 2]), __float_as_uint(S[i + 3]));
      }
    }
    uint8_t* out = p.prob + (size_t)((job_grp(n) * 16 + tile) * kProbBytes);
    float d0 = 0.f, d1 = 0.f;
    if (j == 0) r0 = r1 = 0.f;
    if (__any_sync(0xffffffffu, max(a0, a1) > __float_as_int(kLazyAbove) || max(u0, u1) >= __float_as_uint(-kLazyBelow))) {
      r0 = -INFINITY;
      d0 = S[0];
      d1 = S[2];
#pragma unroll
      for (int i = 0; i < 64; i += 4) {
        d0 = fmaxf(d0, fmaxf(S[i], S[i + 1]));
        d1 = fmaxf(d1, fmaxf(S[i + 2], S[i + 3]));
      }
      d0 = fmaxf(d0, __shfl_xor_sync(0xffffffffu, d0, 1));
      d1 = fmaxf(d1, __shfl_xor_sync(0xffffffffu, d1, 1));
      d0 = fmaxf(d0, __shfl_xor_sync(0xffffffffu, d0, 2));
      d1 = fmaxf(d1, __shfl_xor_sync(0xffffffffu, d1, 2));
#pragma unroll
      for (int i = 0; i < 64; i++) S[i] -= (i & 2) ? d1 : d0;
    }
    float l0 = 0.f, l1 = 0.f;
#pragma unroll
    for (int i = 0; i < 64; i += 4) {
#pragma unroll
      for (int k = 0; k < 4; k++) S[i + k] = ex2(S[i + k]);
      l0 += S[i] + S[i + 1];
      l1 += S[i + 2] + S[i + 3];
    }
    pin(S);
    l0 += __shfl_xor_sync(0xffffffffu, l0, 1);
    l1 += __shfl_xor_sync(0xffffffffu, l1, 1);
    l0 += __shfl_xor_sync(0xffffffffu, l0, 2);
    l1 += __shfl_xor_sync(0xffffffffu, l1, 2);
    uint8_t* dst = out + kProbData + (2 * j + wg) * 16384 + (threadIdx.x & 127) * 16;
#pragma unroll
    for (int i = 0; i < 8; i++)
      asm volatile("st.global.L1::no_allocate.v4.u32 [%0], {%1, %2, %3, %4};" ::"l"(dst + i * 2048),
                   "r"(pack_f16(S[8 * i], S[8 * i + 1])), "r"(pack_f16(S[8 * i + 2], S[8 * i + 3])),
                   "r"(pack_f16(S[8 * i + 4], S[8 * i + 5])), "r"(pack_f16(S[8 * i + 6], S[8 * i + 7]))
                   : "memory");
    l0 *= 0.25f;
    l1 *= 0.25f;
    r0 += l0;
    r1 += l1;
    if ((lane & 3) == 0) {
      *(float4*)(out + kProbExtra + j * 1024 + threadIdx.x * 4) = make_float4(d0, d1, l0, l1);
      if (j == blocks - 1) stg64((uint64_t)(out + threadIdx.x * 2), __float_as_uint(r0), __float_as_uint(r1));
    }
  };
  if (wg == 1) bar_arrive(2);
#pragma unroll 1
  for (n = 0; n < 2; n++) {
    blocks = tail_blocks(job_grp(n));
    wait_long(bars + kFullK, n);
    int tile = 0, j = 0, tile_b = -1, j_b = 0;
#pragma unroll 1
    for (;;) {
      const uint32_t qa = issue(A, tile, tile < 16 ? j : 1);
      wg_wait<1>();
      if (tile_b >= 0) finish(B, tile_b, j_b);
      wg_wait<0>();
      if (tile == 16) break;
      const bool wrap = j == blocks - 1;
      if (wrap && lane == 0) mbar_arrive_local(qa);
      tile_b = tile + wrap;
      j_b = wrap ? 0 : j + 1;
      const uint32_t qb = issue(B, tile_b, j_b);
      wg_wait<1>();
      finish(A, tile, j);
      asm volatile("st.volatile.shared.f32 [%0], %1;" ::"r"(bars + kDummy), "f"(r1) : "memory");
      wg_wait<0>();
      const bool wrap_b = j_b == blocks - 1;
      if (wrap_b && lane == 0) mbar_arrive_local(qb);
      tile = tile_b + wrap_b;
      j = wrap_b ? 0 : j_b + 1;
    }
    __syncwarp();
    if (lane == 0) mbar_arrive_local(bars + kDone);
  }
}

__global__ void __cluster_dims__(2, 1, 1) __launch_bounds__(384, 1)
    attn_kernel(const Params p, const __grid_constant__ CUtensorMap tmq, const __grid_constant__ CUtensorMap tmo) {
  extern __shared__ uint8_t smem_raw[];
  const uint32_t t_start = now_clk();
  const uint32_t sbase = ((uint32_t)__cvta_generic_to_shared(smem_raw) + 1023) & ~1023u;
  if (blockIdx.x >= kOwners) {
    helper_cta(p, tmq, sbase, t_start);
    return;
  }
  const uint32_t bars = sbase + kSmemBar;
  const int grp = blockIdx.x >> 4, mt = blockIdx.x & 15;
  const int tail = __shfl_sync(0xffffffffu, tail_blocks(grp), 0), own = kSteps - tail;
  const uint32_t tail_stage = tail == 3 ? kSmemQ : kSmemV + kTileBytes;
  const int warp = __shfl_sync(0xffffffffu, threadIdx.x >> 5, 0);
  const int lane = threadIdx.x & 31;

  auto load_q = [&](int tile, int w) {
    const uint32_t bar = bars + kBarFullQ + 8 * w;
    const int row = (tile * 8 + grp) * kS + mt * 128 + w * 64;
    mbar_expect_tx(bar, 16384);
    mbar_expect_tx(bars + kBarFullQ2 + 8 * w, 8192);
#pragma unroll
    for (int c = 0; c < 3; c++)
      tma_load_2d(sbase + kSmemQ + w * 24576 + c * 8192, &tmq, c * 64, row, c < 2 ? bar : bars + kBarFullQ2 + 8 * w);
  };
  if (warp == 8 && elect_one()) {
    mbar_init(bars + kBarParams, 1);
    mbar_init(bars + kBarCodes, 1);
    mbar_init(bars + kBarUnits, 1);
    asm volatile("fence.proxy.async.shared::cta;" ::: "memory");
    mbar_expect_tx(bars + kBarParams, 32768);
    bulk_load(sbase + kSmemV, p.ks + grp * 32 * kD, 12288, bars + kBarParams);
    bulk_load(sbase + kSmemV + 12288, p.kz + grp * 32 * kD, 12288, bars + kBarParams);
    bulk_load(sbase + kSmemV + 24576, p.vs + grp * kS, 4096, bars + kBarParams);
    bulk_load(sbase + kSmemV + 36864, p.vz + grp * kS, 4096, bars + kBarParams);
  }
  __syncwarp();
  if (warp == 8) {
    asm volatile("bar.arrive 6, 160;" ::: "memory");
    while (now_clk() - t_start < ((uint32_t)(kCodeDelays >> 8 * grp) & 255) * 32) {}
  }
  const int row_k0 = grp * kS + (blockIdx.x & 1) * 64;
  if (warp == 8 && elect_one()) {
    mbar_expect_tx(bars + kBarUnits, 4 * 6144);
#pragma unroll
    for (int j = 0; j < 4; j++)
      bulk_load(sbase + kSmemK + 3 * kChunkBytes + j * 6144,
                (j & 1 ? p.qv : p.qk) + (size_t)unit_row((j >> 1) + 1 - (j & 1), grp, mt) * kD, 6144, bars + kBarUnits);
    mbar_expect_tx(bars + kBarCodes, kTileBytes);
    bulk_load(sbase + kSmemV + kTileBytes, p.qk + (size_t)row_k0 * kD, kTileBytes, bars + kBarCodes);
    for (int i = 0; i < 2; i++) {
      mbar_init(bars + kBarFullK01 + 8 * i, 1);
      mbar_init(bars + kBarFullV + 8 * i, 1);
      mbar_init(bars + kBarEmptyK12 + 8 * i, 16);
      mbar_init(bars + kBarEmptyV + 8 * i, 16);
      mbar_init(bars + kBarFullQ + 8 * i, 1);
      mbar_init(bars + kBarFullQ2 + 8 * i, 1);
      mbar_init(bars + kBarEmptyQ + 8 * i, 4);
      mbar_init(bars + kBarStage + 8 * i, 4);
      mbar_init(bars + kBarStaged + 8 * i, 4);
      for (int c = 0; c < 3; c++) mbar_init(bars + kBarTail + 24 * i + 8 * c, 4);
    }
    mbar_init(bars + kBarFullK2, 1);
    mbar_init(bars + kBarFullV2, 1);
    mbar_init(bars + kBarEmptyK0, 16);
    asm volatile("st.shared.u32 [%0], %1;" ::"r"(bars + kProgress), "r"(0) : "memory");
    asm volatile("fence.mbarrier_init.release.cluster;" ::: "memory");
    asm volatile("fence.acq_rel.cta;" ::: "memory");
    asm volatile("prefetch.tensormap [%0];" ::"l"(&tmq) : "memory");
  }
  __syncwarp();
  cluster_arrive();
  const bool helper = warp > 8 || (warp >= 4 && warp < 7);
  const uint32_t th = warp < 8 ? threadIdx.x & 127 : threadIdx.x - 288;
  const int it = warp < 8 ? 1 : 0;
  if (warp == 8) {
    while (now_clk() - t_start < ((uint32_t)(kQueryDelays >> 8 * grp) & 255) * 32) {}
#pragma unroll 1
    for (int w = 0; w < 2; w++)
      if (elect_one()) load_q(0, w);
  }
  __syncwarp();
  if (warp < 4) {
    asm volatile("bar.sync 6, 160;" ::: "memory");
    Range r = {make_uint4(~0u, ~0u, ~0u, ~0u), 0u};
    mbar_spin(bars + kBarParams, 0);
    const uint32_t pitch = lane >= 24 ? 128 : kD * 2;
    uint32_t src = sbase + kSmemV + (lane >= 24 ? 24576 - 384 : 0) + lane * 16 + warp * 8 * pitch;
#pragma unroll 1
    for (int j = 0; j < 2; j++) {
      Stat st;
#pragma unroll
      for (int i = 0; i < 4; i++, src += pitch) {
        st.s[i] = lds128(src);
        st.z[i] = lds128(src + 12288);
      }
      stat_add(st, r);
    }
    const uint32_t part = sbase + kSmemV + 40960 + lane * 16;
    sts128(part + warp * 1024, r.lo.x, r.lo.y, r.lo.z, r.lo.w);
    sts128(part + warp * 1024 + 512, r.hi, 0u, 0u, 0u);
    asm volatile("bar.sync 4, 128;" ::: "memory");
#pragma unroll
    for (int j = 1; j < 4; j++) {
      const uint32_t other = part + ((warp + j) & 3) * 1024;
      const uint4 lo = lds128(other);
      r.lo = make_uint4(__vminu2(r.lo.x, lo.x), __vminu2(r.lo.y, lo.y), __vminu2(r.lo.z, lo.z), __vminu2(r.lo.w, lo.w));
      r.hi = __vmaxu2(r.hi, lds64(other + 512).x);
    }
    stat_keep(stat_finish(r, lane), 0, lane, bars);
    __syncwarp();
    if (warp == 0) asm volatile("bar.arrive 5, 224;" ::: "memory");
  }
  if (helper) {
    asm volatile("bar.sync 5, 224;" ::: "memory");
    const uint32_t hi = th >= 48 ? 1 : 0, q = th - hi * 48;
    const uint32_t src = sbase + kSmemK + 3 * kChunkBytes + it * 12288 + hi * 3072 + q * 16;
    const uint32_t kp = sbase + kSmemV + (2 * it + 2 + (mt >> 3)) * (kD * 2) + q * 8;
    const uint32_t vp = sbase + kSmemV + 24576 + (it * kBN + mt * 8 + hi * 4) * 2;
    Unit k0, v0;
    k0.s = lds64(kp);
    k0.z = lds64(kp + 12288);
    v0.s = lds64(vp);
    v0.z = lds64(vp + 12288);
    mbar_spin(bars + kBarUnits, 0);
#pragma unroll
    for (int i = 0; i < 4; i++) {
      k0.x[i] = lds128(src + i * 768);
      v0.x[i] = lds128(src + 6144 + i * 768);
    }
    store_k(unit_dst<false>(p, it + 1, grp, mt, th), 0, th, k0, bars, false);
    store_v(unit_dst<true>(p, it, grp, mt, th), it, v0, bars);
    if (warp < 8) asm volatile("bar.arrive 3, 192;" ::: "memory");
  }
  cluster_wait();
  if (warp < 4) {
    uint2 o0[3], s0[3], z0[3];
#pragma unroll
    for (int c = 0; c < 3; c++) {
      const uint32_t col = c * 128 + (threadIdx.x & 15) * 8;
      o0[c] = lds64(bars + kOffK + col);
      s0[c] = lds64(sbase + kSmemV + (blockIdx.x & 1) * (kD * 2) + col);
      z0[c] = lds64(sbase + kSmemV + 12288 + (blockIdx.x & 1) * (kD * 2) + col);
      s0[c] = make_uint2(k_scale(s0[c].x), k_scale(s0[c].y));
      z0[c] = make_uint2(k_zero(z0[c].x), k_zero(z0[c].y));
    }
    mbar_spin(bars + kBarCodes, 0);
    const uint32_t r = threadIdx.x >> 4, half = sbase + kSmemK + (blockIdx.x & 1) * (kChunkBytes / 2);
    uint32_t src = sbase + kSmemV + kTileBytes + r * 768 + (threadIdx.x & 15) * 16;
    uint32_t dst = half + r * 128 + (threadIdx.x & 1) * 8 + ((((threadIdx.x & 15) >> 1) ^ r) << 4);
#pragma unroll 1
    for (int i = 0; i < 4; i++, src += 16 * 768, dst += 2048) {
      uint4 x[6];
#pragma unroll
      for (int j = 0; j < 6; j++)
        asm volatile("ld.shared.v4.u32 {%0, %1, %2, %3}, [%4];"
                     : "=r"(x[j].x), "=r"(x[j].y), "=r"(x[j].z), "=r"(x[j].w)
                     : "r"(src + (j & 1) * 8 * 768 + (j >> 1) * 256));
#pragma unroll
      for (int j = 0; j < 6; j++)
        asm volatile("st.shared.v2.u32 [%0], {%1, %2};" ::"r"(dst + (j & 1) * 1024 + (j >> 1) * kChunkBytes),
                     "r"(k_pair(codes_bf16(x[j].x, x[j].y), kBf16ScaleK, z0[j >> 1].x, s0[j >> 1].x, o0[j >> 1].x)),
                     "r"(k_pair(codes_bf16(x[j].z, x[j].w), kBf16ScaleK, z0[j >> 1].y, s0[j >> 1].y, o0[j >> 1].y)));
    }
    asm volatile("fence.proxy.async.shared::cta;" ::: "memory");
    asm volatile("bar.sync 4, 128;" ::: "memory");
    if (threadIdx.x == 0) {
      mbar_expect_tx(bars + kBarFullK01, kChunkBytes);
      mbar_expect_tx(bars + kBarFullK2, kChunkBytes / 2);
#pragma unroll
      for (int c = 0; c < 3; c++)
        bulk_copy_peer(half + c * kChunkBytes, kChunkBytes / 2, bars + (c < 2 ? kBarFullK01 : kBarFullK2),
                       (blockIdx.x & 1) ^ 1);
    }
  }

  if (warp >= 8) {
    asm volatile("setmaxnreg.dec.sync.aligned.u32 56;");
    if (warp == 8) {
      const uint32_t rank = blockIdx.x & 1;
      const unsigned* flags = p.flags + grp * kFlagsPerGroup;
      const uint8_t* const images = tile_image(p, 0, grp, 0);
      auto image = [&](int step, uint32_t offset) { return images + ((step & (kRing - 1)) * (2 * kTileBytes) + offset); };
      uint32_t k_dst = sbase + kSmemK + 2 * kChunkBytes + rank * (kChunkBytes / 2);
      auto next_slot = [&]() {
        k_dst += kChunkBytes;
        if (k_dst >= sbase + kSmemV) k_dst -= 5 * kChunkBytes;
        return k_dst;
      };
      auto k_chunk = [&](uint32_t dst, int step, int c, uint32_t bar) {
        bulk_load_mc(dst, image(step, c * kChunkBytes + rank * (kChunkBytes / 2)), kChunkBytes / 2, bar);
      };
      auto load_k01 = [&](int step) {
        const uint32_t bar = bars + kBarFullK01 + 8 * (step & 1);
        const uint32_t d0 = next_slot(), d1 = next_slot();
        if (elect_one()) {
          mbar_expect_tx(bar, 2 * kChunkBytes);
          k_chunk(d0, step, 0, bar);
          k_chunk(d1, step, 1, bar);
        }
        __syncwarp();
      };
      auto load_k2 = [&](int step) {
        const uint32_t d = next_slot();
        if (elect_one()) {
          mbar_expect_tx(bars + kBarFullK2, kChunkBytes);
          k_chunk(d, step, 2, bars + kBarFullK2);
        }
        __syncwarp();
      };
      auto v_part = [&](int step, uint32_t len, uint32_t bar) {
        bulk_load_mc(sbase + kSmemV + (step & 1) * kTileBytes + rank * (len / 2),
                     image(step, kTileBytes + rank * (len / 2)), len / 2, bar);
      };
      auto load_vt = [&](int step) {
        const uint32_t bar = bars + kBarFullV + 8 * (step & 1);
        if (elect_one()) {
          mbar_expect_tx(bar, kTileBytes);
          v_part(step, kTileBytes, bar);
        }
        __syncwarp();
      };
      auto wait_flag = [&](int f) {
        flag_wait(flags + f);
      };
      auto store_out = [&](int tile, int w) {
        mbar_spin(bars + kBarStaged + 8 * w, tile & 1);
        asm volatile("fence.proxy.async.shared::cta;" ::: "memory");
        if (elect_one()) {
          const int row = (tile * 8 + grp) * kS + mt * 128 + w * 64;
#pragma unroll
          for (int c = 0; c < 3; c++)
            tma_store_2d(&tmo, sbase + kSmemV + w * kTileBytes + kTileBytes / 2 + c * 8192, c * 64, row);
          asm volatile("cp.async.bulk.commit_group;" ::: "memory");
        }
        __syncwarp();
      };
      auto reload_v = [&](int w, int step, uint32_t bar) {
        asm volatile("cp.async.bulk.wait_group.read 0;" ::: "memory");
        if (elect_one())
          bulk_load(sbase + kSmemV + w * kTileBytes + kTileBytes / 2, image(step, kTileBytes + kTileBytes / 2), kTileBytes / 2, bar);
        __syncwarp();
      };
      int pf = 3;
      uint32_t pf_at = unit_row(pf, grp, mt) * (kD * 4);
      auto prefetch_next = [&]() {
        const uint32_t at = pf_at;
        pf++;
        pf_at += (pf & 15) ? kBN * kD * 4 : (kBN + 7 * kS) * kD * 4;
        if (elect_one()) {
          prefetch_bulk((const uint8_t*)p.qv + at, 6144);
          if (pf < own) prefetch_bulk((const uint8_t*)p.qk + pf_at, 6144);
        }
        __syncwarp();
      };
      const uint8_t* prob = p.prob + (size_t)(blockIdx.x * kProbBytes);
      const int poll_step = (own - 3) | 1;
      auto load_p = [&](uint32_t dst, int q, uint32_t bar) {
        bulk_load(dst - rank * (kChunkBytes / 2), prob + kProbData + q * kChunkBytes, kChunkBytes, bar);
      };
      wait_flag(1);
      load_k01(1);
#pragma unroll 1
      for (int s = 0;; s++) {
        const bool newq = (s & 15) == 15;
        if (newq) {
          mbar_spin(bars + kBarEmptyQ, (s >> 4) & 1);
          if (elect_one()) load_q((s >> 4) + 1, 0);
          __syncwarp();
        }
        mbar_spin(bars + kBarEmptyK0, s & 1);
        load_k2(s + 1);
        if (s == 0) {
          if (elect_one()) {
            mbar_expect_tx(bars + kBarFullV, kTileBytes / 2);
            mbar_expect_tx(bars + kBarFullV2, kTileBytes / 2);
            v_part(0, kTileBytes / 2, bars + kBarFullV);
            bulk_load_mc(sbase + kSmemV + kTileBytes / 2 + rank * (kTileBytes / 4),
                         image(0, kTileBytes + kTileBytes / 2 + rank * (kTileBytes / 4)), kTileBytes / 4,
                         bars + kBarFullV2);
          }
          __syncwarp();
          prefetch_next();
        }
        const bool tile_end = (s & 15) == 0 && s > 0;
        if (tile_end) {
          store_out((s >> 4) - 1, 0);
          reload_v(0, s, bars + kBarFullV2);
        }
        const int pf_end = min(s + kLead + 2 + (s >= own - 7), kSteps - 1);
        if (pf < pf_end) prefetch_next();
        if (newq) {
          mbar_spin(bars + kBarEmptyQ + 8, (s >> 4) & 1);
          if (elect_one()) load_q((s >> 4) + 1, 1);
          __syncwarp();
        }
        if (s & 1) {
          uint32_t f = grp * kFlagsPerGroup + s + 2;
          if (lane == 31 && s == kStatStep) f = kFlagStats + grp;
          if (lane == 31 && s == poll_step) f = kFlagHelper + grp;
          f *= 4;
          asm("" : "+r"(f));
          flag_wait((const unsigned*)((const uint8_t*)p.flags + f));
        }
        if (s == poll_step && elect_one()) prefetch_bulk(prob, kProbData + tail * 2 * kChunkBytes);
        __syncwarp();
        mbar_spin(bars + kBarEmptyK12 + 8 * (s & 1), (s >> 1) & 1);
        if (s + 2 < own) {
          load_k01(s + 2);
        } else {
          const uint32_t d0 = next_slot(), d1 = next_slot();
          if (elect_one()) {
            mbar_expect_tx(bars + kBarUnits, 2 * kChunkBytes + 512);
            bulk_load(bars + kOffK, prob, 512, bars + kBarUnits);
            load_p(d0, 0, bars + kBarUnits);
            load_p(d1, 1, bars + kBarUnits);
          }
          __syncwarp();
        }
        mbar_spin(bars + kBarEmptyV + 8 * ((s + 1) & 1), (((s + 1) >> 1) & 1) ^ 1);
        if (newq || tile_end) {
          const uint32_t bar = bars + kBarFullV + 8 * ((s + 1) & 1);
          if (elect_one()) {
            mbar_expect_tx(bar, newq ? kTileBytes / 2 : kTileBytes);
            if (newq) mbar_expect_tx(bars + kBarFullV2, kTileBytes / 2);
            v_part(s + 1, kTileBytes / 2, bar);
          }
          __syncwarp();
          if (tile_end) {
            store_out((s >> 4) - 1, 1);
            reload_v(1, s + 1, bar);
          }
        } else {
          load_vt(s + 1);
        }
        if ((s & 15) == kStatStep && s < kSteps - 16) {
          uint4 x;
          asm volatile("ld.global.L1::no_allocate.v4.u32 {%0, %1, %2, %3}, [%4];"
                       : "=r"(x.x), "=r"(x.y), "=r"(x.z), "=r"(x.w)
                       : "l"(p.prob + (kHeadStats + (((s >> 4) + 1) * 8 + grp) * 512 + lane * 16))
                       : "memory");
          stat_keep(x, (s >> 4) + 1, lane, bars);
          __syncwarp();
        }
        asm volatile("st.volatile.shared.u32 [%0], %1;" ::"r"(bars + kProgress), "r"(s + 1) : "memory");
        if (pf <= pf_end && !tile_end) prefetch_next();
        if (s < kSteps - 16) {
          if ((s & 12) == 8) {
            const uint8_t* qn = (const uint8_t*)(p.q + (size_t)((((s >> 4) + 1) * 8 + grp) * kS + mt * 128) * kD);
            if (elect_one()) prefetch_bulk(qn + (s & 3) * 12288, 12288);
            __syncwarp();
          }
        }
        if (s == own - 2) break;
      }
      wait_flag(kSteps - 1);
      uint32_t vw = pick(tail, kPlacesV<1>, kPlacesV<2>, kPlacesV<3>);
      int q = 2;
#pragma unroll 1
      for (int i = 0;; i++) {
        vw >>= 8;
        const uint32_t bar = bars + (vw >> 1 & 0x78);
        mbar_spin(i == 0 ? bars + kBarEmptyK12 + 8 * ((own - 1) & 1) : bar + (kBarEmptyV - kBarFullV),
                  (i == 0 ? own - 1 : (vw ^ 4) >> 1) >> 1 & 1);
        if (i == 1) mbar_spin(bars + kBarFullQ, 0);
        if (elect_one()) {
          mbar_expect_tx(bar, kTileBytes);
          bulk_load_mc(sbase + (vw & 11) * 16384 + rank * (kTileBytes / 2), image(own + i, rank * (kTileBytes / 2)),
                       kTileBytes / 2, bar);
        }
        __syncwarp();
#pragma unroll 1
        for (; q < min(2 * i + 3, 2 * tail); q++) {
          const uint32_t d = next_slot();
          const uint32_t pb = bars + ((kBarCodes | kBarParams << 8 | (kBarFullQ + 8) << 16 | kBarFullQ2 << 24) >> (8 * q - 16) & 255);
          if (elect_one()) {
            mbar_expect_tx(pb, kChunkBytes);
            load_p(d, q, pb);
          }
          __syncwarp();
        }
        if (i == tail - 1) break;
      }
      unsigned done = 0;
      if (lane == 0)
        asm volatile("atom.global.inc.u32 %0, [%1], %2;" : "=r"(done) : "l"(p.flags + kFlagDone), "n"(kOwners - 1) : "memory");
      if (__shfl_sync(0xffffffffu, done, 0) == kOwners - 1) {
#pragma unroll
        for (int j = 0; j < 8 * kFlagsPerGroup / 128; j++) ((uint4*)p.flags)[j * 32 + lane] = make_uint4(0, 0, 0, 0);
        if (lane < 4) ((uint4*)p.flags)[kFlagHelper / 4 + lane] = make_uint4(0, 0, 0, 0);
      }
      __syncwarp();
      cluster_arrive();
#pragma unroll 1
      for (int j = 0; j < 6; j++) {
        const int w = j >= 3 ? 1 : 0;
        mbar_spin(bars + kBarTail + 8 * j, 0);
        asm volatile("fence.proxy.async.shared::cta;" ::: "memory");
        if (elect_one())
          tma_store_2d(&tmo, sbase + tail_stage + j * 8192, (j - 3 * w) * 64,
                       ((kWaves - 1) * 8 + grp) * kS + mt * 128 + w * 64);
        __syncwarp();
      }
      if (elect_one()) asm volatile("cp.async.bulk.commit_group;\ncp.async.bulk.wait_group.read 0;" ::: "memory");

    } else {
      const uint32_t t = threadIdx.x - 288;
      auto throttle = [&](int i) {
#pragma unroll 1
        for (int n = 0; n < 100000; n++) {
          int prog;
          asm volatile("ld.volatile.shared.u32 %0, [%1];" : "=r"(prog) : "r"(bars + kProgress) : "memory");
          if (__all_sync(0xffffffffu, i <= prog + kLead)) break;
          __nanosleep(200);
        }
      };
      asm volatile("bar.sync 3, 192;" ::: "memory");
      publish(p, 1, grp);
      Unit v, k;
      load_unit<false>(p, unit_row(3, grp, mt), t, k);
      load_unit<true>(p, unit_row(2, grp, mt), t, v);
#pragma unroll 1
      for (int i = 2; i < kSteps; i++) {
        throttle(i - (i >= own));
        if (i + 1 < own) store_k(unit_dst<false>(p, i + 1, grp, mt, t), ((i + 1) >> 4) & 1, t, k, bars, codes_are_bytes(k));
        load_unit<false>(p, unit_row(min(i + 2, own - 1), grp, mt), t, k);
        store_v_any(unit_dst<true>(p, i, grp, mt, t, own), i, v, bars);
        if (i & 1) publish(p, i, grp);
        load_unit<true>(p, unit_row(min(i + 1, kSteps - 1), grp, mt), t, v);
      }
    }
  } else {
    asm volatile("setmaxnreg.inc.sync.aligned.u32 224;");
    const int wg = warp >> 2;
    float S[64], O[96];
    uint32_t P[32];
    float m0 = 0.f, m1 = 0.f, l0 = 0.f, l1 = 0.f, h0 = 0.f, h1 = 0.f;
    bool shifted = false;
    auto release = [&](uint32_t bar) {
      if (lane < 2) mbar_arrive_cluster(bar, lane);
    };
    auto stage_o = [&](uint32_t stage, float f0, float f1, int c_lo, int c_hi) {
      const uint32_t addr = stage + ((warp & 3) * 16 + (lane & 15)) * 128 + (((lane >> 4) ^ (lane & 7)) << 4);
#pragma unroll
      for (int j = 4 * c_lo; j < 4 * c_hi; j++) {
        float* o = O + 8 * j;
#pragma unroll
        for (int i = 0; i < 8; i++) o[i] = (i & 2) ? fmaf(o[i], f1, h1) : fmaf(o[i], f0, h0);
        asm volatile("stmatrix.sync.aligned.m8n8.x4.shared.b16 [%0], {%1, %2, %3, %4};" ::"r"(
                         (addr ^ ((j & 3) * 32)) + (j >> 2) * 8192),
                     "r"(pack_bf16(o[0], o[1])), "r"(pack_bf16(o[2], o[3])), "r"(pack_bf16(o[4], o[5])),
                     "r"(pack_bf16(o[6], o[7]))
                     : "memory");
      }
    };
    auto staged = [&]() {
      __syncwarp();
      if (lane == 0) mbar_arrive_local(bars + kBarStaged + 8 * wg);
    };
    float sc0 = 1.f, sc1 = 1.f;
    auto quad_sum = [&](float x) {
      x += __shfl_xor_sync(0xffffffffu, x, 1);
      return x + __shfl_xor_sync(0xffffffffu, x, 2);
    };
    auto finish_l = [&](int wave, float& i0, float& i1) {
      const uint4 vp = lds128(bars + kParV + wave * 32);
      const float a = quad_sum(l0), b = quad_sum(l1);
      i0 = __uint_as_float(vp.z) * rcp(a);
      i1 = __uint_as_float(vp.z) * rcp(b);
      h0 = (a - 2.f * quad_sum(h0)) * i0 * __uint_as_float(vp.y);
      h1 = (b - 2.f * quad_sum(h1)) * i1 * __uint_as_float(vp.y);
    };
    auto issue_qk = [&](int s, int slot0) {
      const uint32_t kb = desc_lo(sbase + kSmemK, 16);
      const uint32_t qb = desc_lo(sbase + kSmemQ, 16) + wg * 1536;
#pragma unroll
      for (int c = 0; c < 3; c++) {
        const int slot = slot0 + c >= 5 ? slot0 + c - 5 : slot0 + c;
        if (c == 2) {
          mbar_wait(bars + kBarFullK2, s & 1);
          if ((s & 15) == 0) mbar_wait(bars + kBarFullQ2 + 8 * wg, (s >> 4) & 1);
        }
#pragma unroll
        for (int kk = 0; kk < 4; kk++)
          wgmma_ss_n128(S, desc64<1024>(qb + c * 512 + kk * 2), desc64<1024>(kb + slot * 1024 + kk * 2),
                        c + kk > 0);
        if (c != 1) wg_commit();
      }
    };
    auto issue_pv = [&](int s) {
      const uint32_t vb = desc_lo(sbase + kSmemV, 1024) + (s & 1) * (kTileBytes >> 4);
      const int acc = (s & 15) != 0;
      auto run = [&](int lo, int hi, int acc0) {
#pragma unroll
        for (int kk = lo; kk < hi; kk++)
          wgmma_rs_n192t(O, P[kk * 4], P[kk * 4 + 1], P[kk * 4 + 2], P[kk * 4 + 3], desc64<3072>(vb + kk * 384),
                         kk > 0 ? 1 : acc0);
      };
      if (acc) {
        wg_fence();
        run(0, 8, 1);
        wg_commit();
      } else {
        wg_fence();
        run(0, 4, 0);
        mbar_wait(bars + kBarFullV2, (s >> 4) & 1);
        wg_fence();
        run(4, 8, 1);
        wg_commit();
      }
    };
    auto shift = [&](int lo, float d0, float d1) {
#pragma unroll
      for (int i = lo; i < 64; i += 4) {
        S[i] -= d0;
        S[i + 1] -= d0;
        S[i + 2] -= d1;
        S[i + 3] -= d1;
      }
    };
    auto unsafe = [&](int lo, int hi, bool first) {
      int a0 = 0, a1 = 0, b0 = 0, b1 = 0;
#pragma unroll
      for (int i = lo; i < hi; i += 8) {
        a0 = __vimax3_s32(a0, __float_as_int(S[i]), __float_as_int(S[i + 1]));
        a1 = __vimax3_s32(a1, __float_as_int(S[i + 2]), __float_as_int(S[i + 3]));
        b0 = __vimax3_s32(b0, __float_as_int(S[i + 4]), __float_as_int(S[i + 5]));
        b1 = __vimax3_s32(b1, __float_as_int(S[i + 6]), __float_as_int(S[i + 7]));
      }
      bool bad = __vimax3_s32(max(a0, b0), a1, b1) > __float_as_int(kLazyAbove);
      if (first) {
        uint32_t u0 = ~0u, u1 = ~0u;
#pragma unroll
        for (int i = 0; i < 16; i += 4) {
          u0 = __vimin3_u32(u0, __float_as_uint(S[i]), __float_as_uint(S[i + 1]));
          u1 = __vimin3_u32(u1, __float_as_uint(S[i + 2]), __float_as_uint(S[i + 3]));
        }
        bad |= max(u0, u1) >= __float_as_uint(-kLazyBelow);
      }
      return __any_sync(0xffffffffu, bad);
    };
    float e0, e1;
    auto use_true_max = [&](int lo, bool first, bool boundary, float& f0, float& f1) {
      float d0 = S[lo], d1 = S[lo + 2];
#pragma unroll
      for (int i = lo; i < 64; i += 4) {
        d0 = fmaxf(d0, fmaxf(S[i], S[i + 1]));
        d1 = fmaxf(d1, fmaxf(S[i + 2], S[i + 3]));
      }
      d0 = fmaxf(d0, __shfl_xor_sync(0xffffffffu, d0, 1));
      d1 = fmaxf(d1, __shfl_xor_sync(0xffffffffu, d1, 1));
      d0 = fmaxf(d0, __shfl_xor_sync(0xffffffffu, d0, 2));
      d1 = fmaxf(d1, __shfl_xor_sync(0xffffffffu, d1, 2));
      if (!first) {
        d0 = fmaxf(d0, 0.f);
        d1 = fmaxf(d1, 0.f);
        f0 = ex2(-d0);
        f1 = ex2(-d1);
        l0 *= f0;
        l1 *= f1;
        if (!boundary) {
          h0 *= f0;
          h1 *= f1;
        }
#pragma unroll
        for (int i = 0; i < lo; i++) S[i] *= (i & 2) ? f1 : f0;
      }
      if (lo > 0) shift(lo, d0, d1);
      e0 = d0;
      e1 = d1;
      m0 += d0;
      m1 += d1;
      shifted = true;
    };
    auto exps = [&](int lo, int hi) {
#pragma unroll
      for (int i = lo; i < hi; i += 4) {
        S[i] = ex2(S[i]);
        S[i + 1] = ex2(S[i + 1]);
        S[i + 2] = ex2(S[i + 2]);
        S[i + 3] = ex2(S[i + 3]);
        l0 += S[i] + S[i + 1];
        l1 += S[i + 2] + S[i + 3];
      }
    };
    auto to_p = [&]() {
#pragma unroll
      for (int j = 0; j < 32; j++) P[j] = pack_f16(S[2 * j], S[2 * j + 1]);
    };
    auto scale_o = [&](float f0, float f1) {
#pragma unroll
      for (int i = 0; i < 96; i += 4) {
        O[i] *= f0;
        O[i + 1] *= f0;
        O[i + 2] *= f1;
        O[i + 3] *= f1;
      }
    };
#pragma unroll
    for (int i = 0; i < 96; i++) asm volatile("" : "=f"(O[i]));
#pragma unroll
    for (int i = 0; i < 32; i++) asm volatile("" : "=r"(P[i]));
    if (threadIdx.x == 128) asm volatile("prefetch.tensormap [%0];" ::"l"(&tmo) : "memory");
    if (wg == 1) bar_arrive(1);
    int slot0 = 2;
#pragma unroll 1
    for (int s = 0;; s++) {
      const bool boundary = (s & 15) == 0;
      slot0 = slot0 >= 2 ? slot0 - 2 : slot0 + 3;
      if (boundary) mbar_wait(bars + kBarFullQ + 8 * wg, (s >> 4) & 1);
      mbar_wait(bars + kBarFullK01 + 8 * (s & 1), (s >> 1) & 1);
      bar_sync(1 + wg);
      pin(P);
      pin(O);
      wg_fence();
      issue_qk(s, slot0);
      mbar_wait(bars + kBarFullV + 8 * ((s - 1) & 1), ((s - 1) >> 1) & 1);
      wg_wait<1>();
      release(bars + kBarEmptyK0);
      if (s > 0) issue_pv(s - 1);
      else wg_commit();
      bar_arrive(2 - wg);
      wg_wait<1>();
      pin(S);
      release(bars + kBarEmptyK12 + 8 * (s & 1));
      if ((s & 15) == 15 && lane == 0) mbar_arrive_local(bars + kBarEmptyQ + 8 * wg);
      bool rescale = false;
      e0 = m0;
      e1 = m1;
#pragma unroll 1
      for (;;) {
        if (shifted) shift(0, e0, e1);
        if (rescale || !unsafe(0, kExpSplit, boundary)) break;
        use_true_max(0, boundary, boundary, sc0, sc1);
        rescale = true;
      }
      const bool late = unsafe(kExpSplit, 64, false);
      exps(0, kExpSplit);
      pin(S);
      asm volatile("st.volatile.shared.f32 [%0], %1;" ::"r"(bars + kDummy), "f"(l0 + l1) : "memory");
      wg_wait<0>();
      pin(O);
      pin(P);
      if (s > 0) {
        release(bars + kBarEmptyV + 8 * ((s - 1) & 1));
        if (((s + wg) & 15) == 0 && lane == 0) mbar_arrive_local(bars + kBarStage + 8 * (1 - wg));
      }
      if (late) {
        float f0, f1;
        use_true_max(kExpSplit, false, boundary, f0, f1);
        if (!boundary) {
          sc0 = f0;
          sc1 = f1;
          rescale = true;
        }
      }
      if (boundary && s > 0) {
        mbar_spin(bars + kBarStage + 8 * wg, ((s >> 4) - 1) & 1);
        stage_o(sbase + kSmemV + wg * kTileBytes + kTileBytes / 2, sc0, sc1, 0, 3);
        staged();
      } else if (rescale && s > 0) {
        scale_o(sc0, sc1);
      }
      pin(S);
      exps(kExpSplit, 64);
      to_p();
      if ((s & 15) == 7) {
        h0 = l0;
        h1 = l1;
      }
      if ((s & 15) == 15) {
        finish_l(s >> 4, sc0, sc1);
        m0 = m1 = l0 = l1 = 0.f;
        shifted = false;
      }
      if (s == own - 1) break;
    }
    uint32_t vw = pick(tail, kPlacesV<1>, kPlacesV<2>, kPlacesV<3>);
    uint32_t pw = wg ? pick(tail, kPlacesP<1, 1>, kPlacesP<2, 1>, kPlacesP<3, 1>)
                     : pick(tail, kPlacesP<1, 0>, kPlacesP<2, 0>, kPlacesP<3, 0>);
    auto next_v = [&]() {
      mbar_spin(bars + (vw >> 1 & 0x78), vw >> 2 & 1);
      const uint32_t vb = desc_lo(sbase, 1024) + (vw & 11) * 1024;
      vw >>= 8;
      return vb;
    };
    bool rescale = false;
    const float4* extra = (const float4*)(p.prob + (size_t)(blockIdx.x * kProbBytes + kProbExtra + (threadIdx.x >> 2) * 16));
    auto next_p = [&]() {
      mbar_spin(bars + (pw >> 1 & 0xF8), pw >> 3 & 1);
      const uint32_t a = sbase + (pw & 7) * 16384 + (threadIdx.x & 127) * 16;
      pw >>= 10;
      if (rescale) {
        const float4 b = __ldcg(extra);
        extra += 64;
        scale_p(a, ex2(b.x - m0), ex2(b.y - m1));
      }
      return a;
    };
    auto take = [&](uint32_t (&A)[32], uint32_t a) {
#pragma unroll
      for (int i = 0; i < 8; i++) {
        const uint4 x = lds128v(a + i * 2048);
        A[4 * i] = x.x, A[4 * i + 1] = x.y, A[4 * i + 2] = x.z, A[4 * i + 3] = x.w;
      }
      pin(A);
    };
    float f0 = 1.f, f1 = 1.f;
    uint32_t pa;
#pragma unroll 1
    for (int x = 0;; x++) {
      const uint32_t vb = next_v();
      bar_sync(1 + wg);
      pin(P);
      pin(O);
      wg_fence();
#pragma unroll
      for (int kk = 0; kk < 8; kk++)
        wgmma_rs_n192t(O, P[kk * 4], P[kk * 4 + 1], P[kk * 4 + 2], P[kk * 4 + 3], desc64<3072>(vb + kk * 384), 1);
      wg_commit();
      if (x < tail - 1) bar_arrive(2 - wg);
      if (x == 0) {
        mbar_spin(bars + kBarUnits, 1);
        const uint2 r = lds64(bars + kOffK + (threadIdx.x >> 2) * 8);
        float r0 = __uint_as_float(r.x), r1 = __uint_as_float(r.y);
        rescale = shifted || __any_sync(0xffffffffu, r0 < 0.f);
        if (rescale) {
          float n0 = m0, n1 = m1;
          r0 = r1 = 0.f;
#pragma unroll 1
          for (int j = 0;; j++) {
            const float4 b = __ldcg(extra + j * 64);
            const float x0 = fmaxf(n0, b.x), x1 = fmaxf(n1, b.y);
            r0 = r0 * ex2(n0 - x0) + b.z * ex2(b.x - x0);
            r1 = r1 * ex2(n1 - x1) + b.w * ex2(b.y - x1);
            n0 = x0;
            n1 = x1;
            if (j == tail - 1) break;
          }
          f0 = ex2(m0 - n0);
          f1 = ex2(m1 - n1);
          l0 *= f0;
          l1 *= f1;
          h0 *= f0;
          h1 *= f1;
          m0 = n0;
          m1 = n1;
        }
        l0 += r0;
        l1 += r1;
        finish_l(kWaves - 1, sc0, sc1);
        asm volatile("st.volatile.shared.f32 [%0], %1;" ::"r"(bars + kDummy), "f"(h0 + h1) : "memory");
      }
      pa = next_p();
      if (x == tail - 1) break;
      wg_wait<0>();
      pin(O);
      pin(P);
      if (rescale && x == 0) {
        scale_o(f0, f1);
        f0 = f1 = 1.f;
      }
      take(P, pa);
      release(bars + kBarEmptyV + 8 * ((own - 1 + x) & 1));
    }
    cluster_arrive();
    uint32_t R[32];
    take(R, pa);
    const uint32_t v_last = next_v();
    float T0[32], T1[32];
    auto tail_pv = [&](float (&T)[32], int c) {
      const uint32_t vb = v_last + c * 64;
      wg_fence();
#pragma unroll
      for (int kk = 0; kk < 8; kk++)
        wgmma_rs_n64t(T, R[kk * 4], R[kk * 4 + 1], R[kk * 4 + 2], R[kk * 4 + 3], desc64<3072>(vb + kk * 384), kk > 0);
      wg_commit();
    };
    uint32_t X[16];
    auto tail_pack = [&](float (&T)[32], int c) {
      pin(T);
#pragma unroll
      for (int i = 0; i < 16; i++) {
        const float f = (i & 1) ? sc1 : sc0;
        X[i] = pack_bf16(fmaf(T[2 * i], f, O[32 * c + 2 * i]), fmaf(T[2 * i + 1], f, O[32 * c + 2 * i + 1]));
      }
      pin(X);
    };
    auto tail_store = [&](int c) {
      const uint32_t addr = sbase + tail_stage + wg * (kTileBytes / 2) + c * 8192 +
                            ((warp & 3) * 16 + (lane & 15)) * 128 + (((lane >> 4) ^ (lane & 7)) << 4);
#pragma unroll
      for (int j = 0; j < 4; j++)
        asm volatile("stmatrix.sync.aligned.m8n8.x4.shared.b16 [%0], {%1, %2, %3, %4};" ::"r"(addr ^ (j * 32)), "r"(X[4 * j]),
                     "r"(X[4 * j + 1]), "r"(X[4 * j + 2]), "r"(X[4 * j + 3])
                     : "memory");
      __syncwarp();
      if (lane == 0) mbar_arrive_local(bars + kBarTail + 24 * wg + 8 * c);
    };
    tail_pv(T0, 0);
    f0 *= sc0;
    f1 *= sc1;
    wg_wait<1>();
    pin(P);
    auto prescale = [&](int c) {
      pin(O);
#pragma unroll
      for (int i = 32 * c; i < 32 * c + 32; i++) O[i] = (i & 2) ? fmaf(O[i], f1, h1) : fmaf(O[i], f0, h0);
      pin(O);
      mbar_spin(bars + kBarEmptyV + 8, 0);
    };
    prescale(0);
    tail_pv(T1, 1);
    if (wg == 0) bar_arrive(2);
    wg_wait<1>();
    tail_pack(T0, 0);
    tail_store(0);
    tail_pv(T0, 2);
    prescale(1);
    wg_wait<1>();
    tail_pack(T1, 1);
    tail_store(1);
    prescale(2);
    wg_wait<0>();
    tail_pack(T0, 2);
    tail_store(2);
    cluster_wait();
  }
}

}

extern "C" void kernel_launch(void* const* d_in, const int* in_sizes, int n_in, void* d_out, int out_size) {
  static CUtensorMap tmq, tmo;
  static const void *tm_q = nullptr, *tm_o = nullptr;
  static void *scratch, *flags, *prob;
  if (tm_q != d_in[0] || tm_o != d_out) {
    typedef CUresult (*EncodeFn)(CUtensorMap*, CUtensorMapDataType, cuuint32_t, void*, const cuuint64_t*,
                                 const cuuint64_t*, const cuuint32_t*, const cuuint32_t*, CUtensorMapInterleave,
                                 CUtensorMapSwizzle, CUtensorMapL2promotion, CUtensorMapFloatOOBfill);
    void* fn = nullptr;
    cudaDriverEntryPointQueryResult qr;
    cudaGetDriverEntryPoint("cuTensorMapEncodeTiled", &fn, cudaEnableDefault, &qr);
    cuuint64_t dims[2] = {(cuuint64_t)kD, (cuuint64_t)kH * kS};
    cuuint64_t strides[1] = {(cuuint64_t)kD * 2};
    cuuint32_t box[2] = {64, 64};
    cuuint32_t estr[2] = {1, 1};
    ((EncodeFn)fn)(&tmq, CU_TENSOR_MAP_DATA_TYPE_BFLOAT16, 2, d_in[0], dims, strides, box, estr,
                   CU_TENSOR_MAP_INTERLEAVE_NONE, CU_TENSOR_MAP_SWIZZLE_128B, CU_TENSOR_MAP_L2_PROMOTION_L2_128B,
                   CU_TENSOR_MAP_FLOAT_OOB_FILL_NONE);
    ((EncodeFn)fn)(&tmo, CU_TENSOR_MAP_DATA_TYPE_BFLOAT16, 2, d_out, dims, strides, box, estr,
                   CU_TENSOR_MAP_INTERLEAVE_NONE, CU_TENSOR_MAP_SWIZZLE_128B, CU_TENSOR_MAP_L2_PROMOTION_NONE,
                   CU_TENSOR_MAP_FLOAT_OOB_FILL_NONE);
    cudaFuncSetAttribute(attn_kernel, cudaFuncAttributeMaxDynamicSharedMemorySize, kSmemTotal);
    cudaGetSymbolAddress(&scratch, g_scratch);
    cudaGetSymbolAddress(&flags, g_flags);
    cudaGetSymbolAddress(&prob, g_prob);
    tm_q = d_in[0];
    tm_o = d_out;
  }
  Params p;
  p.q = (const __nv_bfloat16*)d_in[0];
  p.qk = (const int*)d_in[1];
  p.qv = (const int*)d_in[2];
  p.ks = (const __nv_bfloat16*)d_in[3];
  p.kz = (const __nv_bfloat16*)d_in[4];
  p.vs = (const __nv_bfloat16*)d_in[5];
  p.vz = (const __nv_bfloat16*)d_in[6];
  p.scratch = (uint8_t*)scratch;
  p.flags = (unsigned*)flags;
  p.prob = (uint8_t*)prob;
  attn_kernel<<<kOwners + kHelpers, 384, kSmemTotal>>>(p, tmq, tmo);
}
```

```cpp
#include <cuda_runtime.h>
#include <cuda_bf16.h>
#include <cuda.h>
#include <math.h>
#include <stdint.h>

namespace {

constexpr int kH = 32, kS = 2048, kD = 192;
constexpr int kGroupTok = 64;
constexpr int kBN = 128;
constexpr int kNBlk = kS / kBN;
constexpr int kWaves = 4;
constexpr int kSteps = kWaves * kNBlk;
constexpr int kTileBytes = kBN * kD * 2;
constexpr int kOwners = 128, kHelpers = 4;
constexpr uint32_t kTails = 0x33222112u;
constexpr uint32_t kJobs = 0x30214567u;
constexpr int kMaxTail = 3;
__device__ __forceinline__ int tail_blocks(int grp) { return (kTails >> (4 * grp)) & 3; }
constexpr uint32_t kHelperDelay = 42000, kHelperPrepare = 12000;
constexpr int kProbExtra = 512, kProbData = 4096, kProbBytes = kProbData + 2 * kMaxTail * 16384;
constexpr int kFlagTarget = 48;
constexpr int kFlagsPerGroup = kSteps;
constexpr float kLazyAbove = 15.f, kLazyBelow = 11.f;
constexpr int kLead = 3;
constexpr int kRing = 2 * kLead + 2;
static_assert((kRing & (kRing - 1)) == 0, "power of two");
constexpr int kBarPolls = 1 << 13, kFlagPolls = 1 << 16;

constexpr uint64_t pack_delays(int a, int b, int c, int d, int e, int f, int g, int h) {
  const int t[8] = {a, b, c, d, e, f, g, h};
  uint64_t w = 0;
  for (int i = 0; i < 8; i++) w |= (uint64_t)((t[i] + 16) / 32) << 8 * i;
  return w;
}
constexpr uint64_t kCodeDelays = pack_delays(500, 0, 0, 750, 1000, 1250, 1500, 1750), kQueryDelays = pack_delays(3340, 1900, 2600, 3860, 4380, 4900, 5420, 5940);
constexpr int kStatStep = 9;
static_assert(kStatStep + kLead < 15, "the first block of a head is expanded after its statistics have arrived");
constexpr uint32_t kOffsetFactor = 0x3EA03EA0u;
constexpr int kExpSplit = 32;
constexpr int kChunkBytes = kBN * 128;
constexpr int kSmemQ = 0;
constexpr int kSmemK = kTileBytes;
constexpr int kSmemV = kSmemK + 5 * kChunkBytes;
constexpr int kSmemBar = kSmemV + 2 * kTileBytes;
constexpr int kOffK = 256, kParV = kOffK + 2 * kD * 2, kBarBytes = kParV + 128;
constexpr int kSmemTotal = kSmemBar + kBarBytes + 1024;

constexpr int kBarFullK01 = 0, kBarFullV = 16, kBarEmptyK12 = 32, kBarEmptyV = 48, kBarFullQ = 64, kBarEmptyQ = 80,
              kBarFullK2 = 96, kBarEmptyK0 = 104, kBarStage = 112, kBarStaged = 128, kBarFullV2 = 144,
              kBarFullQ2 = 152, kBarCodes = 168, kBarTail = 176, kProgress = 224, kDummy = 228, kBarParams = 232,
              kBarUnits = 240;

constexpr uint32_t v_places(int n) {
  uint32_t w = (kSmemQ >> 14 | kBarFullQ << 1) << 8;
  for (int x = 0; x <= n; x += x ? 1 : 2) {
    const int v = kSteps - n + x - (x ? 2 : 1);
    w |= ((kSmemV + (v & 1) * kTileBytes) >> 14 | (v & 2) << 1 | (kBarFullV + 8 * (v & 1)) << 1) << 8 * x;
  }
  return w;
}
constexpr uint32_t p_places(int n, int wg) {
  constexpr int bar[6] = {kBarUnits, kBarUnits, kBarCodes, kBarParams, kBarFullQ + 8, kBarFullQ2};
  uint32_t w = 0;
  for (int j = 0; j < n; j++)
    w |= ((kSmemK >> 14) + (3 * (kSteps - n) + 2 * j + wg) % 5 | (j < 2) << 3 | bar[2 * j + wg] << 1) << 10 * j;
  return w;
}
template <int n> constexpr uint32_t kPlacesV = v_places(n);
template <int n, int wg> constexpr uint32_t kPlacesP = p_places(n, wg);
__device__ __forceinline__ uint32_t pick(int n, uint32_t a, uint32_t b, uint32_t c) { return n == 1 ? a : n == 2 ? b : c; }

__device__ __align__(1024) uint4 g_scratch[(size_t)8 * kRing * 2 * kTileBytes / 16];
constexpr int kFlagHelper = 8 * kFlagsPerGroup, kFlagStats = kFlagHelper + 8, kFlagDone = kFlagStats + 8;
__device__ __align__(16) unsigned g_flags[kFlagDone + 1];
constexpr int kHelperImages = kOwners * kProbBytes, kHeadStats = kHelperImages + 8 * kMaxTail * kTileBytes;
__device__ __align__(1024) uint4 g_prob[(kHeadStats + kH * 512) / 16];

__device__ __forceinline__ void wgmma_ss_n128(float (&d)[64], uint64_t da, uint64_t db, int scale_d) {
  asm volatile("{\n.reg .pred p;\nsetp.ne.b32 p, %66, 0;\n"
    "wgmma.mma_async.sync.aligned.m64n128k16.f32.bf16.bf16 "
    "{%0, %1, %2, %3, %4, %5, %6, %7, %8, %9, %10, %11, %12, %13, %14, %15, %16, %17, %18, %19, %20, %21, %22, %23, %24, %25, %26, %27, %28, %29, %30, %31, %32, %33, %34, %35, %36, %37, %38, %39, %40, %41, %42, %43, %44, %45, %46, %47, %48, %49, %50, %51, %52, %53, %54, %55, %56, %57, %58, %59, %60, %61, %62, %63}, %64, %65, p, 1, 1, 0, 0;\n}\n"
    : "+f"(d[0]), "+f"(d[1]), "+f"(d[2]), "+f"(d[3]), "+f"(d[4]), "+f"(d[5]), "+f"(d[6]), "+f"(d[7]), "+f"(d[8]), "+f"(d[9]), "+f"(d[10]), "+f"(d[11]), "+f"(d[12]), "+f"(d[13]), "+f"(d[14]), "+f"(d[15]), "+f"(d[16]), "+f"(d[17]), "+f"(d[18]), "+f"(d[19]), "+f"(d[20]), "+f"(d[21]), "+f"(d[22]), "+f"(d[23]), "+f"(d[24]), "+f"(d[25]), "+f"(d[26]), "+f"(d[27]), "+f"(d[28]), "+f"(d[29]), "+f"(d[30]), "+f"(d[31]), "+f"(d[32]), "+f"(d[33]), "+f"(d[34]), "+f"(d[35]), "+f"(d[36]), "+f"(d[37]), "+f"(d[38]), "+f"(d[39]), "+f"(d[40]), "+f"(d[41]), "+f"(d[42]), "+f"(d[43]), "+f"(d[44]), "+f"(d[45]), "+f"(d[46]), "+f"(d[47]), "+f"(d[48]), "+f"(d[49]), "+f"(d[50]), "+f"(d[51]), "+f"(d[52]), "+f"(d[53]), "+f"(d[54]), "+f"(d[55]), "+f"(d[56]), "+f"(d[57]), "+f"(d[58]), "+f"(d[59]), "+f"(d[60]), "+f"(d[61]), "+f"(d[62]), "+f"(d[63])
    : "l"(da), "l"(db), "r"(scale_d));
}
__device__ __forceinline__ void wgmma_new_n128(float (&d)[64], uint64_t da, uint64_t db) {
  asm volatile("{\n.reg .pred p;\nsetp.ne.b32 p, 0, 0;\n"
    "wgmma.mma_async.sync.aligned.m64n128k16.f32.bf16.bf16 "
    "{%0, %1, %2, %3, %4, %5, %6, %7, %8, %9, %10, %11, %12, %13, %14, %15, %16, %17, %18, %19, %20, %21, %22, %23, %24, %25, %26, %27, %28, %29, %30, %31, %32, %33, %34, %35, %36, %37, %38, %39, %40, %41, %42, %43, %44, %45, %46, %47, %48, %49, %50, %51, %52, %53, %54, %55, %56, %57, %58, %59, %60, %61, %62, %63}, %64, %65, p, 1, 1, 0, 0;\n}\n"
    : "=f"(d[0]), "=f"(d[1]), "=f"(d[2]), "=f"(d[3]), "=f"(d[4]), "=f"(d[5]), "=f"(d[6]), "=f"(d[7]), "=f"(d[8]), "=f"(d[9]), "=f"(d[10]), "=f"(d[11]), "=f"(d[12]), "=f"(d[13]), "=f"(d[14]), "=f"(d[15]), "=f"(d[16]), "=f"(d[17]), "=f"(d[18]), "=f"(d[19]), "=f"(d[20]), "=f"(d[21]), "=f"(d[22]), "=f"(d[23]), "=f"(d[24]), "=f"(d[25]), "=f"(d[26]), "=f"(d[27]), "=f"(d[28]), "=f"(d[29]), "=f"(d[30]), "=f"(d[31]), "=f"(d[32]), "=f"(d[33]), "=f"(d[34]), "=f"(d[35]), "=f"(d[36]), "=f"(d[37]), "=f"(d[38]), "=f"(d[39]), "=f"(d[40]), "=f"(d[41]), "=f"(d[42]), "=f"(d[43]), "=f"(d[44]), "=f"(d[45]), "=f"(d[46]), "=f"(d[47]), "=f"(d[48]), "=f"(d[49]), "=f"(d[50]), "=f"(d[51]), "=f"(d[52]), "=f"(d[53]), "=f"(d[54]), "=f"(d[55]), "=f"(d[56]), "=f"(d[57]), "=f"(d[58]), "=f"(d[59]), "=f"(d[60]), "=f"(d[61]), "=f"(d[62]), "=f"(d[63])
    : "l"(da), "l"(db));
}
__device__ __forceinline__ void wgmma_rs_n64t(float (&d)[32], uint32_t a0, uint32_t a1, uint32_t a2, uint32_t a3, uint64_t db, int scale_d) {
  asm volatile("{\n.reg .pred p;\nsetp.ne.b32 p, %37, 0;\n"
    "wgmma.mma_async.sync.aligned.m64n64k16.f32.f16.f16 "
    "{%0, %1, %2, %3, %4, %5, %6, %7, %8, %9, %10, %11, %12, %13, %14, %15, %16, %17, %18, %19, %20, %21, %22, %23, %24, %25, %26, %27, %28, %29, %30, %31}, {%32, %33, %34, %35}, %36, p, 1, 1, 1;\n}\n"
    : "+f"(d[0]), "+f"(d[1]), "+f"(d[2]), "+f"(d[3]), "+f"(d[4]), "+f"(d[5]), "+f"(d[6]), "+f"(d[7]), "+f"(d[8]), "+f"(d[9]), "+f"(d[10]), "+f"(d[11]), "+f"(d[12]), "+f"(d[13]), "+f"(d[14]), "+f"(d[15]), "+f"(d[16]), "+f"(d[17]), "+f"(d[18]), "+f"(d[19]), "+f"(d[20]), "+f"(d[21]), "+f"(d[22]), "+f"(d[23]), "+f"(d[24]), "+f"(d[25]), "+f"(d[26]), "+f"(d[27]), "+f"(d[28]), "+f"(d[29]), "+f"(d[30]), "+f"(d[31])
    : "r"(a0), "r"(a1), "r"(a2), "r"(a3), "l"(db), "r"(scale_d));
}
__device__ __forceinline__ void wgmma_rs_n192t(float (&d)[96], uint32_t a0, uint32_t a1, uint32_t a2, uint32_t a3, uint64_t db, int scale_d) {
  asm volatile("{\n.reg .pred p;\nsetp.ne.b32 p, %101, 0;\n"
    "wgmma.mma_async.sync.aligned.m64n192k16.f32.f16.f16 "
    "{%0, %1, %2, %3, %4, %5, %6, %7, %8, %9, %10, %11, %12, %13, %14, %15, %16, %17, %18, %19, %20, %21, %22, %23, %24, %25, %26, %27, %28, %29, %30, %31, %32, %33, %34, %35, %36, %37, %38, %39, %40, %41, %42, %43, %44, %45, %46, %47, %48, %49, %50, %51, %52, %53, %54, %55, %56, %57, %58, %59, %60, %61, %62, %63, %64, %65, %66, %67, %68, %69, %70, %71, %72, %73, %74, %75, %76, %77, %78, %79, %80, %81, %82, %83, %84, %85, %86, %87, %88, %89, %90, %91, %92, %93, %94, %95}, {%96, %97, %98, %99}, %100, p, 1, 1, 1;\n}\n"
    : "+f"(d[0]), "+f"(d[1]), "+f"(d[2]), "+f"(d[3]), "+f"(d[4]), "+f"(d[5]), "+f"(d[6]), "+f"(d[7]), "+f"(d[8]), "+f"(d[9]), "+f"(d[10]), "+f"(d[11]), "+f"(d[12]), "+f"(d[13]), "+f"(d[14]), "+f"(d[15]), "+f"(d[16]), "+f"(d[17]), "+f"(d[18]), "+f"(d[19]), "+f"(d[20]), "+f"(d[21]), "+f"(d[22]), "+f"(d[23]), "+f"(d[24]), "+f"(d[25]), "+f"(d[26]), "+f"(d[27]), "+f"(d[28]), "+f"(d[29]), "+f"(d[30]), "+f"(d[31]), "+f"(d[32]), "+f"(d[33]), "+f"(d[34]), "+f"(d[35]), "+f"(d[36]), "+f"(d[37]), "+f"(d[38]), "+f"(d[39]), "+f"(d[40]), "+f"(d[41]), "+f"(d[42]), "+f"(d[43]), "+f"(d[44]), "+f"(d[45]), "+f"(d[46]), "+f"(d[47]), "+f"(d[48]), "+f"(d[49]), "+f"(d[50]), "+f"(d[51]), "+f"(d[52]), "+f"(d[53]), "+f"(d[54]), "+f"(d[55]), "+f"(d[56]), "+f"(d[57]), "+f"(d[58]), "+f"(d[59]), "+f"(d[60]), "+f"(d[61]), "+f"(d[62]), "+f"(d[63]), "+f"(d[64]), "+f"(d[65]), "+f"(d[66]), "+f"(d[67]), "+f"(d[68]), "+f"(d[69]), "+f"(d[70]), "+f"(d[71]), "+f"(d[72]), "+f"(d[73]), "+f"(d[74]), "+f"(d[75]), "+f"(d[76]), "+f"(d[77]), "+f"(d[78]), "+f"(d[79]), "+f"(d[80]), "+f"(d[81]), "+f"(d[82]), "+f"(d[83]), "+f"(d[84]), "+f"(d[85]), "+f"(d[86]), "+f"(d[87]), "+f"(d[88]), "+f"(d[89]), "+f"(d[90]), "+f"(d[91]), "+f"(d[92]), "+f"(d[93]), "+f"(d[94]), "+f"(d[95])
    : "r"(a0), "r"(a1), "r"(a2), "r"(a3), "l"(db), "r"(scale_d));
}

__device__ __forceinline__ uint32_t desc_lo(uint32_t addr, uint32_t lbo) { return ((addr & 0x3FFFF) >> 4) | ((lbo >> 4) << 16); }
template <uint32_t SBO>
__device__ __forceinline__ uint64_t desc64(uint32_t lo) {
  uint64_t d;
  asm("mov.b64 %0, {%1, %2};" : "=l"(d) : "r"(lo), "n"((SBO >> 4) | (1u << 30)));
  return d;
}
__device__ __forceinline__ void wg_fence() { asm volatile("wgmma.fence.sync.aligned;" ::: "memory"); }
__device__ __forceinline__ void wg_commit() { asm volatile("wgmma.commit_group.sync.aligned;" ::: "memory"); }
template <int N>
__device__ __forceinline__ void wg_wait() { asm volatile("wgmma.wait_group.sync.aligned %0;" ::"n"(N) : "memory"); }
__device__ __forceinline__ void bar_sync(int id) { asm volatile("bar.sync %0, 256;" ::"r"(id) : "memory"); }
__device__ __forceinline__ void bar_arrive(int id) { asm volatile("bar.arrive %0, 256;" ::"r"(id) : "memory"); }

template <int N>
__device__ __forceinline__ void pin(float (&r)[N]) {
#pragma unroll
  for (int i = 0; i < N; i++) asm volatile("" : "+f"(r[i])::"memory");
}
template <int N>
__device__ __forceinline__ void pin(uint32_t (&r)[N]) {
#pragma unroll
  for (int i = 0; i < N; i++) asm volatile("" : "+r"(r[i])::"memory");
}

__device__ __forceinline__ void mbar_init(uint32_t bar, uint32_t count) {
  asm volatile("mbarrier.init.shared::cta.b64 [%0], %1;" ::"r"(bar), "r"(count) : "memory");
}
__device__ __forceinline__ void mbar_expect_tx(uint32_t bar, uint32_t bytes) {
  asm volatile("mbarrier.arrive.expect_tx.shared::cta.b64 _, [%0], %1;" ::"r"(bar), "r"(bytes) : "memory");
}
__device__ __forceinline__ void mbar_arrive_local(uint32_t bar) {
  asm volatile("mbarrier.arrive.shared::cta.b64 _, [%0];" ::"r"(bar) : "memory");
}
__device__ __forceinline__ void mbar_arrive_cluster(uint32_t bar, uint32_t cta) {
  asm volatile(
      "{\n.reg .b32 ra;\nmapa.shared::cluster.u32 ra, %0, %1;\n"
      "mbarrier.arrive.shared::cluster.b64 _, [ra];\n}" ::"r"(bar),
      "r"(cta)
      : "memory");
}
__device__ __forceinline__ bool mbar_try(uint32_t bar, uint32_t parity) {
  uint32_t ok;
  asm volatile(
      "{\n.reg .pred p;\nmbarrier.try_wait.parity.shared::cta.b64 p, [%1], %2;\nselp.u32 %0, 1, 0, p;\n}"
      : "=r"(ok)
      : "r"(bar), "r"(parity)
      : "memory");
  return ok;
}
__device__ __forceinline__ uint32_t now_clk() {
  uint32_t t;
  asm volatile("mov.u32 %0, %%clock;" : "=r"(t));
  return t;
}
__device__ __forceinline__ void mbar_wait(uint32_t bar, uint32_t parity) {
  if (mbar_try(bar, parity)) return;
#pragma unroll 1
  for (int n = now_clk() & 1; n < kBarPolls; n++)
    if (mbar_try(bar, parity)) break;
}
__device__ __forceinline__ void mbar_spin(uint32_t bar, uint32_t parity) {
#pragma unroll 1
  for (int n = 0; n < kBarPolls; n++)
    if (mbar_try(bar, parity)) break;
}
__device__ __forceinline__ bool elect_one() {
  uint32_t r;
  asm volatile("{\n.reg .pred p;\nelect.sync _|p, 0xffffffff;\nselp.u32 %0, 1, 0, p;\n}" : "=r"(r));
  return r;
}
__device__ __forceinline__ void bulk_load(uint32_t dst, const void* src, uint32_t bytes, uint32_t bar) {
  asm volatile("cp.async.bulk.shared::cluster.global.mbarrier::complete_tx::bytes [%0], [%1], %2, [%3];" ::"r"(dst),
               "l"(src), "r"(bytes), "r"(bar)
               : "memory");
}
__device__ __forceinline__ void bulk_copy_peer(uint32_t addr, uint32_t bytes, uint32_t bar, uint32_t cta) {
  asm volatile(
      "{\n.reg .b32 ra, rb;\nmapa.shared::cluster.u32 ra, %0, %3;\nmapa.shared::cluster.u32 rb, %2, %3;\n"
      "cp.async.bulk.shared::cluster.shared::cta.mbarrier::complete_tx::bytes [ra], [%0], %1, [rb];\n}" ::"r"(addr),
      "r"(bytes), "r"(bar), "r"(cta)
      : "memory");
}
__device__ __forceinline__ void bulk_load_mc(uint32_t dst, const void* src, uint32_t bytes, uint32_t bar) {
  asm volatile(
      "cp.async.bulk.shared::cluster.global.mbarrier::complete_tx::bytes.multicast::cluster [%0], [%1], %2, [%3], "
      "%4;" ::"r"(dst),
      "l"(src), "r"(bytes), "r"(bar), "h"((uint16_t)3)
      : "memory");
}
constexpr uint64_t kEvictFirst = 0x12F0000000000000ull;
__device__ __forceinline__ void tma_load_2d(uint32_t dst, const CUtensorMap* map, int c0, int c1, uint32_t bar) {
  asm volatile(
      "cp.async.bulk.tensor.2d.shared::cluster.global.mbarrier::complete_tx::bytes.L2::cache_hint [%0], [%1, {%3, %4}], "
      "[%2], %5;" ::"r"(dst),
      "l"(map), "r"(bar), "r"(c0), "r"(c1), "l"(kEvictFirst)
      : "memory");
}
__device__ __forceinline__ void tma_store_2d(const CUtensorMap* map, uint32_t src, int c0, int c1) {
  asm volatile("cp.async.bulk.tensor.2d.global.shared::cta.bulk_group [%0, {%2, %3}], [%1];" ::"l"(map), "r"(src),
               "r"(c0), "r"(c1)
               : "memory");
}
__device__ __forceinline__ void cluster_arrive() { asm volatile("barrier.cluster.arrive.relaxed;" ::: "memory"); }
__device__ __forceinline__ void cluster_wait() { asm volatile("barrier.cluster.wait;" ::: "memory"); }
__device__ __forceinline__ float ex2(float x) {
  float y;
  asm("ex2.approx.ftz.f32 %0, %1;" : "=f"(y) : "f"(x));
  return y;
}
__device__ __forceinline__ float rcp(float x) {
  float y;
  asm("rcp.approx.ftz.f32 %0, %1;" : "=f"(y) : "f"(x));
  return y;
}
__device__ __forceinline__ uint32_t pack_bf16(float lo, float hi) {
  uint32_t r;
  asm("cvt.rn.bf16x2.f32 %0, %1, %2;" : "=r"(r) : "f"(hi), "f"(lo));
  return r;
}

__device__ __forceinline__ uint32_t pack_f16(float lo, float hi) {
  uint32_t r;
  asm("cvt.rn.f16x2.f32 %0, %1, %2;" : "=r"(r) : "f"(hi), "f"(lo));
  return r;
}

__device__ __forceinline__ uint32_t scale_f16(uint32_t w, float f) {
  float x, y;
  asm("{\n.reg .b16 a, b;\nmov.b32 {a, b}, %2;\ncvt.f32.f16 %0, a;\ncvt.f32.f16 %1, b;\n}" : "=f"(x), "=f"(y) : "r"(w));
  return pack_f16(x * f, y * f);
}

struct Params {
  const int* qk;
  const int* qv;
  const __nv_bfloat16* ks;
  const __nv_bfloat16* kz;
  const __nv_bfloat16* vs;
  const __nv_bfloat16* vz;
  const __nv_bfloat16* q;
  uint8_t* scratch;
  unsigned* flags;
  uint8_t* prob;
};

__device__ __forceinline__ int unit_row(int step, int grp, int mt) {
  return ((step >> 4) * 8 + grp) * kS + (step & 15) * kBN + mt * 8;
}
__device__ __forceinline__ uint8_t* tile_image(const Params& p, int step, int grp, int is_v) {
  return p.scratch + ((size_t)(grp * kRing + (unsigned)step % kRing) * 2 + is_v) * kTileBytes;
}
struct Unit { uint4 x[4]; uint2 s, z; };

__device__ __forceinline__ uint4 ldg128(const void* a) {
  uint4 v;
  asm volatile("ld.global.nc.L1::no_allocate.v4.u32 {%0, %1, %2, %3}, [%4];"
               : "=r"(v.x), "=r"(v.y), "=r"(v.z), "=r"(v.w)
               : "l"(a)
               : "memory");
  return v;
}
__device__ __forceinline__ uint4 ldg128_last_use(const void* a) {
  uint4 v;
  asm volatile("ld.global.nc.L1::no_allocate.L2::cache_hint.v4.u32 {%0, %1, %2, %3}, [%4], %5;"
               : "=r"(v.x), "=r"(v.y), "=r"(v.z), "=r"(v.w)
               : "l"(a), "l"(kEvictFirst)
               : "memory");
  return v;
}
__device__ __forceinline__ uint2 ldg64(const void* a) {
  uint2 v;
  asm volatile("ld.global.nc.v2.u32 {%0, %1}, [%2];" : "=r"(v.x), "=r"(v.y) : "l"(a));
  return v;
}
__device__ __forceinline__ void stg64(uint64_t a, uint32_t x, uint32_t y) {
  asm volatile("st.global.v2.u32 [%0], {%1, %2};" ::"l"(a), "r"(x), "r"(y) : "memory");
}
__device__ __forceinline__ uint32_t bf2_mul(uint32_t a, uint32_t b) {
  uint32_t r;
  asm("mul.rn.bf16x2 %0, %1, %2;" : "=r"(r) : "r"(a), "r"(b));
  return r;
}
__device__ __forceinline__ uint32_t bf2_fma(uint32_t a, uint32_t b, uint32_t c) {
  uint32_t r;
  asm("fma.rn.bf16x2 %0, %1, %2, %3;" : "=r"(r) : "r"(a), "r"(b), "r"(c));
  return r;
}
__device__ __forceinline__ uint32_t h2_fma(uint32_t a, uint32_t b, uint32_t c) {
  uint32_t r;
  asm("fma.rn.f16x2 %0, %1, %2, %3;" : "=r"(r) : "r"(a), "r"(b), "r"(c));
  return r;
}
__device__ __forceinline__ uint32_t h2_mul(uint32_t a, uint32_t b) {
  uint32_t r;
  asm("mul.rn.f16x2 %0, %1, %2;" : "=r"(r) : "r"(a), "r"(b));
  return r;
}
__device__ __forceinline__ float bf_lo(uint32_t w) { return __uint_as_float(w << 16); }
__device__ __forceinline__ float bf_hi(uint32_t w) { return __uint_as_float(w & 0xffff0000u); }
__device__ __forceinline__ uint32_t codes_bf16(uint32_t a, uint32_t b) { return pack_bf16((float)(int)a, (float)(int)b); }
__device__ __forceinline__ uint2 lds64(uint32_t a) {
  uint2 v;
  asm volatile("ld.shared.v2.u32 {%0, %1}, [%2];" : "=r"(v.x), "=r"(v.y) : "r"(a));
  return v;
}
__device__ __forceinline__ uint4 lds128(uint32_t a) {
  uint4 v;
  asm volatile("ld.shared.v4.u32 {%0, %1, %2, %3}, [%4];" : "=r"(v.x), "=r"(v.y), "=r"(v.z), "=r"(v.w) : "r"(a));
  return v;
}
__device__ __forceinline__ uint4 lds128v(uint32_t a) {
  uint4 v;
  asm volatile("ld.shared.v4.u32 {%0, %1, %2, %3}, [%4];" : "=r"(v.x), "=r"(v.y), "=r"(v.z), "=r"(v.w) : "r"(a) : "memory");
  return v;
}
__device__ __forceinline__ void scale_p(uint32_t a, float f0, float f1) {
#pragma unroll 1
  for (int i = 0; i < 16; i++, a += i & 1 ? 8 : 2040) {
    const uint2 x = lds64(a);
    asm volatile("st.shared.v2.u32 [%0], {%1, %2};" ::"r"(a), "r"(scale_f16(x.x, f0)), "r"(scale_f16(x.y, f1)) : "memory");
  }
}
__device__ __forceinline__ uint32_t k_scale(uint32_t s) { return bf2_fma(s, 0x40D540D5u, bf2_mul(s, 0x3BEE3BEEu)); }
__device__ __forceinline__ uint32_t k_zero(uint32_t z) { return bf2_mul(z, 0xBC80BC80u); }
__device__ __forceinline__ uint32_t k_pair(uint32_t x, uint32_t xs, uint32_t z, uint32_t s, uint32_t off) {
  return bf2_fma(bf2_fma(x, xs, z), s, off);
}
constexpr uint32_t kByteScaleK = 0x7F007F00u, kBf16ScaleK = 0x3C803C80u, kByteScaleV = 0x60006000u;
template <bool kIsV>
__device__ __forceinline__ void load_unit(const Params& p, int row0, uint32_t t, Unit& d) {
  const uint32_t hi = t >= 48 ? 1 : 0, q = t - hi * 48;
  const uint8_t* src = (const uint8_t*)((kIsV ? p.qv : p.qk) + (size_t)row0 * kD) + (hi * 3072 + q * 16);
#pragma unroll
  for (int i = 0; i < 4; i++) d.x[i] = ldg128_last_use(src + i * 768);
  if (kIsV) {
    uint32_t o = hi * 8;
    asm("" : "+r"(o));
    d.s = ldg64((const uint8_t*)(p.vs + row0) + o);
    d.z = ldg64((const uint8_t*)(p.vz + row0) + o);
  } else {
    d.s = ldg64((const uint8_t*)(p.ks + (row0 / kGroupTok) * kD) + q * 8);
    d.z = ldg64((const uint8_t*)(p.kz + (row0 / kGroupTok) * kD) + q * 8);
  }
}
__device__ __forceinline__ bool codes_are_bytes(const Unit& d, uint32_t a = 0) {
#pragma unroll
  for (int i = 0; i < 4; i++) a |= d.x[i].x | d.x[i].y | d.x[i].z | d.x[i].w;
  return !__any_sync(0xffffffffu, a > 255);
}
template <int kHalf>
__device__ __forceinline__ uint32_t dup16(uint32_t w) {
  uint32_t v;
  if (kHalf == 0) asm("{\n.reg .b16 a, b;\nmov.b32 {a, b}, %1;\nmov.b32 %0, {a, a};\n}" : "=r"(v) : "r"(w));
  else asm("{\n.reg .b16 a, b;\nmov.b32 {a, b}, %1;\nmov.b32 %0, {b, b};\n}" : "=r"(v) : "r"(w));
  return v;
}
template <bool kIsV>
__device__ __forceinline__ uint64_t unit_dst(const Params& p, int step, int grp, int mt, uint32_t t, int own = kSteps) {
  const uint32_t hi = t >= 48 ? 1 : 0, q = t - hi * 48;
  return (uint64_t)(tile_image(p, step, grp, kIsV && step < own) + mt * (kIsV ? 3072 : 1024)) +
         ((q >> 4) * (kIsV ? 1024 : kChunkBytes) + hi * 512 + (q & 1) * 8 + ((((q & 15) >> 1) ^ (hi * 4)) << 4));
}
__device__ __forceinline__ void store_k(uint64_t dst, int slot, uint32_t t, const Unit& d, uint32_t bars, bool bytes) {
  const uint2 off = lds64(bars + kOffK + slot * (kD * 2) + (t >= 48 ? t - 48 : t) * 8);
  uint32_t x[8];
  if (bytes) {
#pragma unroll
    for (int i = 0; i < 4; i++) {
      x[2 * i] = d.x[i].y * 65536u + d.x[i].x;
      x[2 * i + 1] = d.x[i].w * 65536u + d.x[i].z;
    }
  } else {
#pragma unroll
    for (int i = 0; i < 4; i++) {
      x[2 * i] = codes_bf16(d.x[i].x, d.x[i].y);
      x[2 * i + 1] = codes_bf16(d.x[i].z, d.x[i].w);
    }
  }
  const uint32_t xs = bytes ? kByteScaleK : kBf16ScaleK;
  const uint32_t s0 = k_scale(d.s.x), s1 = k_scale(d.s.y), z0 = k_zero(d.z.x), z1 = k_zero(d.z.y);
#pragma unroll
  for (int i = 0; i < 4; i++)
    stg64((dst ^ (i * 16)) + i * 128, k_pair(x[2 * i], xs, z0, s0, off.x), k_pair(x[2 * i + 1], xs, z1, s1, off.y));
}
constexpr uint32_t kCentreBits = 256 * 0x10001u;
constexpr float kCentre = 256 * (1.f / 16777216);
__device__ __forceinline__ void store_v(uint64_t dst, int step, const Unit& d, uint32_t bars) {
  const uint2 par = lds64(bars + kParV + (step >> 4) * 32);
  const float alpha = __uint_as_float(par.x), centre = __uint_as_float(par.y ^ (step & 8) << 28);
#pragma unroll
  for (int i = 0; i < 4; i++) {
    const uint32_t zw = i < 2 ? d.z.x : d.z.y, sw = i < 2 ? d.s.x : d.s.y;
    const uint32_t zz = (i & 1) ? dup16<1>(zw) : dup16<0>(zw), ss = (i & 1) ? dup16<1>(sw) : dup16<0>(sw);
    auto pair = [&](uint32_t a, uint32_t b) {
      uint32_t v;
      asm("{\n.reg .b32 t;\nsub.rn.bf16x2 t, %1, %2;\nmul.rn.bf16x2 %0, t, %3;\n}"
          : "=r"(v)
          : "r"(codes_bf16(a, b)), "r"(zz), "r"(ss));
      return pack_f16(fmaf(bf_lo(v), alpha, centre), fmaf(bf_hi(v), alpha, centre));
    };
    stg64((dst ^ (i * 16)) + i * 128, pair(d.x[i].x, d.x[i].y), pair(d.x[i].z, d.x[i].w));
  }
}
__device__ __forceinline__ void store_v_any(uint64_t dst, int step, const Unit& d, uint32_t bars) {
  const uint2 par = lds64(bars + kParV + (step >> 4) * 32 + 16);
  const uint32_t z0 = d.z.x - 0x40004000u, z1 = d.z.y - 0x40004000u;
  if (!codes_are_bytes(d, ((z0 | z1) & 0xFC00FC00u) | ((d.s.x | d.s.y) & 0x80008000u)) || par.x == 0) {
    store_v(dst, step, d, bars);
    return;
  }
  const uint2 z = make_uint2(z0 * 8 + 0x84008400u, z1 * 8 + 0x84008400u);
  const uint2 s = make_uint2(h2_mul(d.s.x * 8 + par.y, par.x), h2_mul(d.s.y * 8 + par.y, par.x));
  const uint32_t c2 = kCentreBits ^ (step & 8) * 0x10001000u;
#pragma unroll
  for (int i = 0; i < 4; i++) {
    const uint32_t zw = i < 2 ? z.x : z.y, sw = i < 2 ? s.x : s.y;
    const uint32_t zz = (i & 1) ? dup16<1>(zw) : dup16<0>(zw), ss = (i & 1) ? dup16<1>(sw) : dup16<0>(sw);
    stg64((dst ^ (i * 16)) + i * 128, h2_fma(h2_fma(d.x[i].y * 65536u + d.x[i].x, kByteScaleV, zz), ss, c2),
          h2_fma(h2_fma(d.x[i].w * 65536u + d.x[i].z, kByteScaleV, zz), ss, c2));
  }
}
struct Stat { uint4 s[4], z[4]; };
struct Range { uint4 lo; uint32_t hi; };
__device__ __forceinline__ void stat_load(const Params& p, int head, int j, uint32_t lane, Stat& d) {
  const bool v = lane >= 24;
  const uint32_t off = v ? (head * kS + j * 256) * 2 + (lane - 24) * 16 : (head * 32 + j * 4) * (kD * 2) + lane * 16;
  const uint32_t step = v ? 128 : kD * 2;
  const uint8_t *ps = (const uint8_t*)(v ? p.vs : p.ks), *pz = (const uint8_t*)(v ? p.vz : p.kz);
#pragma unroll
  for (int i = 0; i < 4; i++) {
    uint32_t o = off + i * step;
    asm("" : "+r"(o));
    d.s[i] = ldg128(ps + o);
    d.z[i] = ldg128(pz + o);
  }
}
__device__ __forceinline__ uint32_t range2(uint32_t s, uint32_t z) {
  uint32_t r;
  asm("{\n.reg .b32 m;\nmax.xorsign.abs.bf16x2 m, %2, %3;\nmul.rn.bf16x2 %0, %1, m;\n}"
      : "=r"(r)
      : "r"(s), "r"(z), "r"(0x3F803F80u));
  return r & 0x7fff7fffu;
}
__device__ __forceinline__ void stat_add(const Stat& d, Range& r) {
  auto col = [&](uint32_t& lo, uint32_t a, uint32_t b, uint32_t c, uint32_t e) {
    lo = __vimin3_u16x2(__vimin3_u16x2(lo, a, b), c, e);
    r.hi = __vimax3_u16x2(__vimax3_u16x2(r.hi, a, b), c, e);
  };
  col(r.lo.x, range2(d.s[0].x, d.z[0].x), range2(d.s[1].x, d.z[1].x), range2(d.s[2].x, d.z[2].x), range2(d.s[3].x, d.z[3].x));
  col(r.lo.y, range2(d.s[0].y, d.z[0].y), range2(d.s[1].y, d.z[1].y), range2(d.s[2].y, d.z[2].y), range2(d.s[3].y, d.z[3].y));
  col(r.lo.z, range2(d.s[0].z, d.z[0].z), range2(d.s[1].z, d.z[1].z), range2(d.s[2].z, d.z[2].z), range2(d.s[3].z, d.z[3].z));
  col(r.lo.w, range2(d.s[0].w, d.z[0].w), range2(d.s[1].w, d.z[1].w), range2(d.s[2].w, d.z[2].w), range2(d.s[3].w, d.z[3].w));
}
__device__ __forceinline__ void sts128(uint32_t a, uint32_t x, uint32_t y, uint32_t z, uint32_t w) {
  asm volatile("st.shared.v4.u32 [%0], {%1, %2, %3, %4};" ::"r"(a), "r"(x), "r"(y), "r"(z), "r"(w) : "memory");
}
__device__ __forceinline__ uint4 stat_finish(const Range& r, uint32_t lane) {
  const bool v = lane >= 24;
  const uint32_t lo = __vimin3_u16x2(__vminu2(r.lo.x, r.lo.y), r.lo.z, r.lo.w);
  const float amin = bf_hi(__reduce_min_sync(0xffffffffu, v ? min(lo, lo << 16) : ~0u));
  const float amax = fmaxf(bf_hi(__reduce_max_sync(0xffffffffu, v ? max(r.hi, r.hi << 16) : 0u)), 1e-30f);
  const bool centred = amax <= 2.f * amin && amax <= 1e30f;
  const uint32_t a15 = __float_as_uint(__fdividef(centred ? 0.98f * kCentre * 32768 : 16.f * 32768, amax)) & 0xFFFFE000u;
  const float alpha = __uint_as_float(a15) * (1.f / 32768);
  if (lane == 24)
    return make_uint4(__float_as_uint(alpha), centred ? __float_as_uint(kCentre) : 0u, __float_as_uint(__fdividef(1.f, alpha)), 0u);
  if (v) return make_uint4(centred ? (0x3C00u | (a15 >> 13 & 0x3FFu)) * 0x10001u : 0u, ((a15 >> 23) - 239u) * 0x4000400u, 0u, 0u);
  return make_uint4(bf2_mul(r.lo.x, kOffsetFactor), bf2_mul(r.lo.y, kOffsetFactor), bf2_mul(r.lo.z, kOffsetFactor),
                    bf2_mul(r.lo.w, kOffsetFactor));
}
__device__ __forceinline__ void stat_keep(const uint4& x, int wave, uint32_t lane, uint32_t bars) {
  if (lane < 26)
    sts128(bars + lane * 16 + (lane < 24 ? kOffK + (wave & 1) * (kD * 2) : kParV - 24 * 16 + wave * 32), x.x, x.y, x.z, x.w);
}
__device__ __forceinline__ void prefetch_bulk(const void* g, uint32_t bytes) {
  asm volatile("cp.async.bulk.prefetch.L2.global [%0], %1;" ::"l"(g), "r"(bytes) : "memory");
}
__device__ __forceinline__ void publish(const Params& p, int flag, int grp, int warps) {
  asm volatile(
      "{\n.reg .pred p;\nelect.sync _|p, 0xffffffff;\n@p red.release.gpu.global.add.u32 [%0], %1;\n}" ::"l"(
          p.flags + grp * kFlagsPerGroup + flag),
      "r"(warps)
      : "memory");
}
__device__ __forceinline__ void flag_wait(const unsigned* f) {
#pragma unroll 1
  for (int n = 0; n < kFlagPolls; n++) {
    unsigned v;
    asm volatile("ld.acquire.gpu.global.u32 %0, [%1];" : "=r"(v) : "l"(f) : "memory");
    if (__all_sync(0xffffffffu, v >= kFlagTarget)) break;
  }
  asm volatile("fence.proxy.async.global;" ::: "memory");
}

__device__ __forceinline__ void helper_cta(const Params& p, const CUtensorMap& tmq, uint32_t sbase, uint32_t t_start) {
  constexpr int kFullQ = 0, kEmptyQ = 32, kDone = 64, kFullK = 72;
  const uint32_t bars = sbase + kSmemBar, sq = sbase + kMaxTail * kTileBytes;
  const int warp = __shfl_sync(0xffffffffu, threadIdx.x >> 5, 0);
  const int lane = threadIdx.x & 31;
  const int grp0 = blockIdx.x - kOwners;
  auto job_grp = [&](int n) { return (int)(kJobs >> (16 * n + 4 * grp0) & 7); };
  auto job_row = [&](int n) { return ((kWaves - 1) * 8 + job_grp(n)) * kS; };
  auto job_images = [&](int n) { return p.prob + (size_t)(kHelperImages + job_grp(n) * (kMaxTail * kTileBytes)); };
  if (threadIdx.x == 0) {
    for (int i = 0; i < 3; i++) {
      mbar_init(bars + kFullQ + 8 * i, 1);
      mbar_init(bars + kEmptyQ + 8 * i, 4);
    }
    mbar_init(bars + kDone, 8);
    mbar_init(bars + kFullK, 1);
    asm volatile("fence.proxy.async.shared::cta;" ::: "memory");
  }
  auto sleep_until = [&](uint32_t t) {
    while (now_clk() - t_start < t) __nanosleep(200);
  };
  auto wait_long = [&](uint32_t bar, uint32_t parity) {
#pragma unroll 1
    for (int k = 0; k < kFlagPolls && !mbar_try(bar, parity); k++) __nanosleep(200);
  };
  sleep_until(kHelperPrepare);
  if (warp < 6) {
    const int head = job_row(warp & 1) / kS - (warp >> 1) * 8, blocks = tail_blocks(head & 7);
    if (warp < 2 && elect_one()) prefetch_bulk(p.qk + (size_t)(head * kS + kS - blocks * kBN) * kD, blocks * 2 * kTileBytes);
    __syncwarp();
    Range r = {make_uint4(~0u, ~0u, ~0u, ~0u), 0u};
#pragma unroll 1
    for (int j = 0; j < 8; j += 2) {
      Stat a, b;
      stat_load(p, head, j, lane, a);
      stat_load(p, head, j + 1, lane, b);
      stat_add(a, r);
      stat_add(b, r);
    }
    const uint4 x = stat_finish(r, lane);
    if (warp < 2) stat_keep(x, warp, lane, bars);
    *(uint4*)(p.prob + kHeadStats + head * 512 + lane * 16) = x;
  }
  __syncthreads();
  if (threadIdx.x < 2)
    asm volatile("red.release.gpu.global.add.u32 [%0], %1;" ::"l"(p.flags + kFlagStats + job_grp(threadIdx.x)), "n"(kFlagTarget)
                 : "memory");
#pragma unroll 1
  for (int n = 0; n < 2; n++) {
    const int team = warp / 3, units = 16 * tail_blocks(job_grp(n));
    const uint32_t t = threadIdx.x - team * 96, hi = t >= 48 ? 1 : 0, q = t - hi * 48;
    const int row = job_row(n) + kS - units * 8;
    const uint64_t dst = (uint64_t)job_images(n) +
                         ((q >> 4) * kChunkBytes + hi * 512 + (q & 1) * 8 + ((((q & 15) >> 1) ^ (hi * 4)) << 4));
    auto unit_at = [&](int m) { return (m >> 4) * kTileBytes + (m & 15) * 1024; };
#pragma unroll 1
    for (int m = 4 * team; m < units; m += 16) {
      Unit u[4];
#pragma unroll
      for (int i = 0; i < 4; i++) load_unit<false>(p, row + (m + i) * 8, t, u[i]);
#pragma unroll
      for (int i = 0; i < 4; i++) store_k(dst + unit_at(m + i), n, t, u[i], bars, codes_are_bytes(u[i]));
    }
  }
  __threadfence();
  __syncthreads();
  if (warp >= 8) {
    asm volatile("setmaxnreg.dec.sync.aligned.u32 104;");
    if (warp == 8) {
      sleep_until(kHelperDelay);
      uint32_t slot = 0, parity = 1;
#pragma unroll 1
      for (int z = 0; z < 64; z++) {
        const int n = z >> 5, blocks = tail_blocks(job_grp(n));
        if (z == 0 || z == 35) {
          if (n) mbar_spin(bars + kDone, 0);
          asm volatile("fence.proxy.async.global;" ::: "memory");
          if (elect_one()) {
            mbar_expect_tx(bars + kFullK, blocks * kTileBytes);
            bulk_load(sbase, job_images(n), blocks * kTileBytes, bars + kFullK);
          }
          __syncwarp();
        }
        const int half = blocks == 1 ? (z & 28) + (z & 1) * 2 + ((z >> 1) & 1) : z & 31;
        const uint32_t bar = bars + kFullQ + 8 * slot;
        mbar_spin(bars + kEmptyQ + 8 * slot, parity);
        if (elect_one()) {
          mbar_expect_tx(bar, kTileBytes / 2);
#pragma unroll
          for (int c = 0; c < 3; c++)
            tma_load_2d(sq + slot * (kTileBytes / 2) + c * 8192, &tmq, c * 64, job_row(n) + half * 64, bar);
          const int v = min(z + 2 * 3, 63);
          prefetch_bulk(p.q + (size_t)(job_row(v >> 5) + (v & 31) * 64) * kD, kTileBytes / 2);
          if (z == 24) prefetch_bulk(job_images(1), tail_blocks(job_grp(1)) * kTileBytes);
        }
        __syncwarp();
        if (++slot == 3) {
          slot = 0;
          parity ^= 1;
        }
      }
    } else if (warp == 9) {
#pragma unroll 1
      for (int n = 0; n < 2; n++) {
        wait_long(bars + kDone, n);
        if (elect_one()) {
          asm volatile("red.release.gpu.global.add.u32 [%0], %1;" ::"l"(p.flags + kFlagHelper + job_grp(n)), "n"(kFlagTarget)
                       : "memory");
        }
        __syncwarp();
      }
    }
    return;
  }
  asm volatile("setmaxnreg.inc.sync.aligned.u32 200;");
  const int wg = warp >> 2;
  float A[64], B[64];
#pragma unroll
  for (int i = 0; i < 64; i++) asm volatile("" : "=f"(A[i]), "=f"(B[i]));
  int n, blocks;
  auto issue = [&](float (&S)[64], int tile, int j) {
    const uint32_t z = 32 * n + (blocks == 1 ? (tile >> 1) * 4 + 2 * wg + (tile & 1) : 2 * tile + wg);
    const uint32_t turn = z * 43 >> 7, slot = z - 3 * turn;
    if (j == 0) mbar_wait(bars + kFullQ + 8 * slot, turn & 1);
    const uint32_t kb = desc_lo(sbase, 16) + j * (kTileBytes >> 4);
    const uint32_t qb = desc_lo(sq, 16) + slot * (kTileBytes >> 5);
    bar_sync(2 + wg);
    wg_fence();
    wgmma_new_n128(S, desc64<1024>(qb), desc64<1024>(kb));
#pragma unroll
    for (int kk = 1; kk < 12; kk++)
      wgmma_ss_n128(S, desc64<1024>(qb + (kk >> 2) * 512 + (kk & 3) * 2), desc64<1024>(kb + (kk >> 2) * 1024 + (kk & 3) * 2), 1);
    wg_commit();
    bar_arrive(3 - wg);
    return bars + kEmptyQ + 8 * slot;
  };
  float r0, r1;
  auto finish = [&](float (&S)[64], int tile, int j) {
    pin(S);
    int a0 = 0, a1 = 0;
    uint32_t u0 = ~0u, u1 = ~0u;
#pragma unroll
    for (int i = 0; i < 64; i += 4) {
      a0 = __vimax3_s32(a0, __float_as_int(S[i]), __float_as_int(S[i + 1]));
      a1 = __vimax3_s32(a1, __float_as_int(S[i + 2]), __float_as_int(S[i + 3]));
      if (i < 16) {
        u0 = __vimin3_u32(u0, __float_as_uint(S[i]), __float_as_uint(S[i + 1]));
        u1 = __vimin3_u32(u1, __float_as_uint(S[i + 2]), __float_as_uint(S[i + 3]));
      }
    }
    uint8_t* out = p.prob + (size_t)((job_grp(n) * 16 + tile) * kProbBytes);
    float d0 = 0.f, d1 = 0.f;
    if (j == 0) r0 = r1 = 0.f;
    if (__any_sync(0xffffffffu, max(a0, a1) > __float_as_int(kLazyAbove) || max(u0, u1) >= __float_as_uint(-kLazyBelow))) {
      r0 = -INFINITY;
      d0 = S[0];
      d1 = S[2];
#pragma unroll
      for (int i = 0; i < 64; i += 4) {
        d0 = fmaxf(d0, fmaxf(S[i], S[i + 1]));
        d1 = fmaxf(d1, fmaxf(S[i + 2], S[i + 3]));
      }
      d0 = fmaxf(d0, __shfl_xor_sync(0xffffffffu, d0, 1));
      d1 = fmaxf(d1, __shfl_xor_sync(0xffffffffu, d1, 1));
      d0 = fmaxf(d0, __shfl_xor_sync(0xffffffffu, d0, 2));
      d1 = fmaxf(d1, __shfl_xor_sync(0xffffffffu, d1, 2));
#pragma unroll
      for (int i = 0; i < 64; i++) S[i] -= (i & 2) ? d1 : d0;
    }
    float l0 = 0.f, l1 = 0.f;
#pragma unroll
    for (int i = 0; i < 64; i += 4) {
#pragma unroll
      for (int k = 0; k < 4; k++) S[i + k] = ex2(S[i + k]);
      l0 += S[i] + S[i + 1];
      l1 += S[i + 2] + S[i + 3];
    }
    pin(S);
    l0 += __shfl_xor_sync(0xffffffffu, l0, 1);
    l1 += __shfl_xor_sync(0xffffffffu, l1, 1);
    l0 += __shfl_xor_sync(0xffffffffu, l0, 2);
    l1 += __shfl_xor_sync(0xffffffffu, l1, 2);
    uint8_t* dst = out + kProbData + (2 * j + wg) * 16384 + (threadIdx.x & 127) * 16;
#pragma unroll
    for (int i = 0; i < 8; i++)
      asm volatile("st.global.L1::no_allocate.v4.u32 [%0], {%1, %2, %3, %4};" ::"l"(dst + i * 2048),
                   "r"(pack_f16(S[8 * i], S[8 * i + 1])), "r"(pack_f16(S[8 * i + 2], S[8 * i + 3])),
                   "r"(pack_f16(S[8 * i + 4], S[8 * i + 5])), "r"(pack_f16(S[8 * i + 6], S[8 * i + 7]))
                   : "memory");
    l0 *= 0.25f;
    l1 *= 0.25f;
    r0 += l0;
    r1 += l1;
    if ((lane & 3) == 0) {
      *(float4*)(out + kProbExtra + j * 1024 + threadIdx.x * 4) = make_float4(d0, d1, l0, l1);
      if (j == blocks - 1) stg64((uint64_t)(out + threadIdx.x * 2), __float_as_uint(r0), __float_as_uint(r1));
    }
  };
  if (wg == 1) bar_arrive(2);
#pragma unroll 1
  for (n = 0; n < 2; n++) {
    blocks = tail_blocks(job_grp(n));
    wait_long(bars + kFullK, n);
    int tile = 0, j = 0, tile_b = -1, j_b = 0;
#pragma unroll 1
    for (;;) {
      const uint32_t qa = issue(A, tile, tile < 16 ? j : 1);
      wg_wait<1>();
      if (tile_b >= 0) finish(B, tile_b, j_b);
      wg_wait<0>();
      if (tile == 16) break;
      const bool wrap = j == blocks - 1;
      if (wrap && lane == 0) mbar_arrive_local(qa);
      tile_b = tile + wrap;
      j_b = wrap ? 0 : j + 1;
      const uint32_t qb = issue(B, tile_b, j_b);
      wg_wait<1>();
      finish(A, tile, j);
      asm volatile("st.volatile.shared.f32 [%0], %1;" ::"r"(bars + kDummy), "f"(r1) : "memory");
      wg_wait<0>();
      const bool wrap_b = j_b == blocks - 1;
      if (wrap_b && lane == 0) mbar_arrive_local(qb);
      tile = tile_b + wrap_b;
      j = wrap_b ? 0 : j_b + 1;
    }
    __syncwarp();
    if (lane == 0) mbar_arrive_local(bars + kDone);
  }
}

__global__ void __cluster_dims__(2, 1, 1) __launch_bounds__(384, 1)
    attn_kernel(const Params p, const __grid_constant__ CUtensorMap tmq, const __grid_constant__ CUtensorMap tmo) {
  extern __shared__ uint8_t smem_raw[];
  const uint32_t t_start = now_clk();
  const uint32_t sbase = ((uint32_t)__cvta_generic_to_shared(smem_raw) + 1023) & ~1023u;
  if (blockIdx.x >= kOwners) {
    helper_cta(p, tmq, sbase, t_start);
    return;
  }
  const uint32_t bars = sbase + kSmemBar;
  const int grp = blockIdx.x >> 4, mt = blockIdx.x & 15;
  const int tail = __shfl_sync(0xffffffffu, tail_blocks(grp), 0), own = kSteps - tail;
  const uint32_t tail_stage = tail == 3 ? kSmemQ : kSmemV + kTileBytes;
  const int warp = __shfl_sync(0xffffffffu, threadIdx.x >> 5, 0);
  const int lane = threadIdx.x & 31;

  auto load_q = [&](int tile, int w) {
    const uint32_t bar = bars + kBarFullQ + 8 * w;
    const int row = (tile * 8 + grp) * kS + mt * 128 + w * 64;
    mbar_expect_tx(bar, 16384);
    mbar_expect_tx(bars + kBarFullQ2 + 8 * w, 8192);
#pragma unroll
    for (int c = 0; c < 3; c++)
      tma_load_2d(sbase + kSmemQ + w * 24576 + c * 8192, &tmq, c * 64, row, c < 2 ? bar : bars + kBarFullQ2 + 8 * w);
  };
  if (warp == 8 && elect_one()) {
    mbar_init(bars + kBarParams, 1);
    mbar_init(bars + kBarCodes, 1);
    mbar_init(bars + kBarUnits, 1);
    asm volatile("fence.proxy.async.shared::cta;" ::: "memory");
    mbar_expect_tx(bars + kBarParams, 32768);
    bulk_load(sbase + kSmemV, p.ks + grp * 32 * kD, 12288, bars + kBarParams);
    bulk_load(sbase + kSmemV + 12288, p.kz + grp * 32 * kD, 12288, bars + kBarParams);
    bulk_load(sbase + kSmemV + 24576, p.vs + grp * kS, 4096, bars + kBarParams);
    bulk_load(sbase + kSmemV + 36864, p.vz + grp * kS, 4096, bars + kBarParams);
  }
  __syncwarp();
  if (warp == 8) {
    asm volatile("bar.arrive 6, 160;" ::: "memory");
    while (now_clk() - t_start < ((uint32_t)(kCodeDelays >> 8 * grp) & 255) * 32) {}
  }
  const int row_k0 = grp * kS + (blockIdx.x & 1) * 64;
  if (warp == 8 && elect_one()) {
    mbar_expect_tx(bars + kBarUnits, 4 * 6144);
#pragma unroll
    for (int j = 0; j < 4; j++)
      bulk_load(sbase + kSmemK + 3 * kChunkBytes + j * 6144,
                (j & 1 ? p.qv : p.qk) + (size_t)unit_row((j >> 1) + 1 - (j & 1), grp, mt) * kD, 6144, bars + kBarUnits);
    mbar_expect_tx(bars + kBarCodes, kTileBytes);
    bulk_load(sbase + kSmemV + kTileBytes, p.qk + (size_t)row_k0 * kD, kTileBytes, bars + kBarCodes);
    for (int i = 0; i < 2; i++) {
      mbar_init(bars + kBarFullK01 + 8 * i, 1);
      mbar_init(bars + kBarFullV + 8 * i, 1);
      mbar_init(bars + kBarEmptyK12 + 8 * i, 16);
      mbar_init(bars + kBarEmptyV + 8 * i, 16);
      mbar_init(bars + kBarFullQ + 8 * i, 1);
      mbar_init(bars + kBarFullQ2 + 8 * i, 1);
      mbar_init(bars + kBarEmptyQ + 8 * i, 4);
      mbar_init(bars + kBarStage + 8 * i, 4);
      mbar_init(bars + kBarStaged + 8 * i, 4);
      for (int c = 0; c < 3; c++) mbar_init(bars + kBarTail + 24 * i + 8 * c, 4);
    }
    mbar_init(bars + kBarFullK2, 1);
    mbar_init(bars + kBarFullV2, 1);
    mbar_init(bars + kBarEmptyK0, 16);
    asm volatile("st.shared.u32 [%0], %1;" ::"r"(bars + kProgress), "r"(0) : "memory");
    asm volatile("fence.mbarrier_init.release.cluster;" ::: "memory");
    asm volatile("fence.acq_rel.cta;" ::: "memory");
    asm volatile("prefetch.tensormap [%0];" ::"l"(&tmq) : "memory");
  }
  __syncwarp();
  cluster_arrive();
  const bool helper = warp > 8 || (warp >= 4 && warp < 7);
  const uint32_t th = warp < 8 ? threadIdx.x & 127 : threadIdx.x - 288;
  const int it = warp < 8 ? 1 : 0;
  if (warp == 8) {
    while (now_clk() - t_start < ((uint32_t)(kQueryDelays >> 8 * grp) & 255) * 32) {}
#pragma unroll 1
    for (int w = 0; w < 2; w++)
      if (elect_one()) load_q(0, w);
  }
  __syncwarp();
  if (warp < 4) {
    asm volatile("bar.sync 6, 160;" ::: "memory");
    Range r = {make_uint4(~0u, ~0u, ~0u, ~0u), 0u};
    mbar_spin(bars + kBarParams, 0);
    const uint32_t pitch = lane >= 24 ? 128 : kD * 2;
    uint32_t src = sbase + kSmemV + (lane >= 24 ? 24576 - 384 : 0) + lane * 16 + warp * 8 * pitch;
#pragma unroll 1
    for (int j = 0; j < 2; j++) {
      Stat st;
#pragma unroll
      for (int i = 0; i < 4; i++, src += pitch) {
        st.s[i] = lds128(src);
        st.z[i] = lds128(src + 12288);
      }
      stat_add(st, r);
    }
    const uint32_t part = sbase + kSmemV + 40960 + lane * 16;
    sts128(part + warp * 1024, r.lo.x, r.lo.y, r.lo.z, r.lo.w);
    sts128(part + warp * 1024 + 512, r.hi, 0u, 0u, 0u);
    asm volatile("bar.sync 4, 128;" ::: "memory");
#pragma unroll
    for (int j = 1; j < 4; j++) {
      const uint32_t other = part + ((warp + j) & 3) * 1024;
      const uint4 lo = lds128(other);
      r.lo = make_uint4(__vminu2(r.lo.x, lo.x), __vminu2(r.lo.y, lo.y), __vminu2(r.lo.z, lo.z), __vminu2(r.lo.w, lo.w));
      r.hi = __vmaxu2(r.hi, lds64(other + 512).x);
    }
    stat_keep(stat_finish(r, lane), 0, lane, bars);
    __syncwarp();
    if (warp == 0) asm volatile("bar.arrive 5, 224;" ::: "memory");
  }
  if (helper) {
    asm volatile("bar.sync 5, 224;" ::: "memory");
    const uint32_t hi = th >= 48 ? 1 : 0, q = th - hi * 48;
    const uint32_t src = sbase + kSmemK + 3 * kChunkBytes + it * 12288 + hi * 3072 + q * 16;
    const uint32_t kp = sbase + kSmemV + (2 * it + 2 + (mt >> 3)) * (kD * 2) + q * 8;
    const uint32_t vp = sbase + kSmemV + 24576 + (it * kBN + mt * 8 + hi * 4) * 2;
    Unit k0, v0;
    k0.s = lds64(kp);
    k0.z = lds64(kp + 12288);
    v0.s = lds64(vp);
    v0.z = lds64(vp + 12288);
    mbar_spin(bars + kBarUnits, 0);
#pragma unroll
    for (int i = 0; i < 4; i++) {
      k0.x[i] = lds128(src + i * 768);
      v0.x[i] = lds128(src + 6144 + i * 768);
    }
    store_k(unit_dst<false>(p, it + 1, grp, mt, th), 0, th, k0, bars, false);
    store_v(unit_dst<true>(p, it, grp, mt, th), it, v0, bars);
    if (warp < 8) asm volatile("bar.arrive 3, 192;" ::: "memory");
  }
  cluster_wait();
  if (warp < 4) {
    uint2 o0[3], s0[3], z0[3];
#pragma unroll
    for (int c = 0; c < 3; c++) {
      const uint32_t col = c * 128 + (threadIdx.x & 15) * 8;
      o0[c] = lds64(bars + kOffK + col);
      s0[c] = lds64(sbase + kSmemV + (blockIdx.x & 1) * (kD * 2) + col);
      z0[c] = lds64(sbase + kSmemV + 12288 + (blockIdx.x & 1) * (kD * 2) + col);
      s0[c] = make_uint2(k_scale(s0[c].x), k_scale(s0[c].y));
      z0[c] = make_uint2(k_zero(z0[c].x), k_zero(z0[c].y));
    }
    mbar_spin(bars + kBarCodes, 0);
    const uint32_t r = threadIdx.x >> 4, half = sbase + kSmemK + (blockIdx.x & 1) * (kChunkBytes / 2);
    uint32_t src = sbase + kSmemV + kTileBytes + r * 768 + (threadIdx.x & 15) * 16;
    uint32_t dst = half + r * 128 + (threadIdx.x & 1) * 8 + ((((threadIdx.x & 15) >> 1) ^ r) << 4);
#pragma unroll 1
    for (int i = 0; i < 4; i++, src += 16 * 768, dst += 2048) {
      uint4 x[6];
#pragma unroll
      for (int j = 0; j < 6; j++)
        asm volatile("ld.shared.v4.u32 {%0, %1, %2, %3}, [%4];"
                     : "=r"(x[j].x), "=r"(x[j].y), "=r"(x[j].z), "=r"(x[j].w)
                     : "r"(src + (j & 1) * 8 * 768 + (j >> 1) * 256));
#pragma unroll
      for (int j = 0; j < 6; j++)
        asm volatile("st.shared.v2.u32 [%0], {%1, %2};" ::"r"(dst + (j & 1) * 1024 + (j >> 1) * kChunkBytes),
                     "r"(k_pair(codes_bf16(x[j].x, x[j].y), kBf16ScaleK, z0[j >> 1].x, s0[j >> 1].x, o0[j >> 1].x)),
                     "r"(k_pair(codes_bf16(x[j].z, x[j].w), kBf16ScaleK, z0[j >> 1].y, s0[j >> 1].y, o0[j >> 1].y)));
    }
    asm volatile("fence.proxy.async.shared::cta;" ::: "memory");
    asm volatile("bar.sync 4, 128;" ::: "memory");
    if (threadIdx.x == 0) {
      mbar_expect_tx(bars + kBarFullK01, kChunkBytes);
      mbar_expect_tx(bars + kBarFullK2, kChunkBytes / 2);
#pragma unroll
      for (int c = 0; c < 3; c++)
        bulk_copy_peer(half + c * kChunkBytes, kChunkBytes / 2, bars + (c < 2 ? kBarFullK01 : kBarFullK2),
                       (blockIdx.x & 1) ^ 1);
    }
  }

  if (warp >= 8) {
    asm volatile("setmaxnreg.dec.sync.aligned.u32 56;");
    if (warp == 8) {
      const uint32_t rank = blockIdx.x & 1;
      const unsigned* flags = p.flags + grp * kFlagsPerGroup;
      const uint8_t* const images = tile_image(p, 0, grp, 0);
      auto image = [&](int step, uint32_t offset) { return images + ((step & (kRing - 1)) * (2 * kTileBytes) + offset); };
      uint32_t k_dst = sbase + kSmemK + 2 * kChunkBytes + rank * (kChunkBytes / 2);
      auto next_slot = [&]() {
        k_dst += kChunkBytes;
        if (k_dst >= sbase + kSmemV) k_dst -= 5 * kChunkBytes;
        return k_dst;
      };
      auto k_chunk = [&](uint32_t dst, int step, int c, uint32_t bar) {
        bulk_load_mc(dst, image(step, c * kChunkBytes + rank * (kChunkBytes / 2)), kChunkBytes / 2, bar);
      };
      auto load_k01 = [&](int step) {
        const uint32_t bar = bars + kBarFullK01 + 8 * (step & 1);
        const uint32_t d0 = next_slot(), d1 = next_slot();
        if (elect_one()) {
          mbar_expect_tx(bar, 2 * kChunkBytes);
          k_chunk(d0, step, 0, bar);
          k_chunk(d1, step, 1, bar);
        }
        __syncwarp();
      };
      auto load_k2 = [&](int step) {
        const uint32_t d = next_slot();
        if (elect_one()) {
          mbar_expect_tx(bars + kBarFullK2, kChunkBytes);
          k_chunk(d, step, 2, bars + kBarFullK2);
        }
        __syncwarp();
      };
      auto v_part = [&](int step, uint32_t len, uint32_t bar) {
        bulk_load_mc(sbase + kSmemV + (step & 1) * kTileBytes + rank * (len / 2),
                     image(step, kTileBytes + rank * (len / 2)), len / 2, bar);
      };
      auto load_vt = [&](int step) {
        const uint32_t bar = bars + kBarFullV + 8 * (step & 1);
        if (elect_one()) {
          mbar_expect_tx(bar, kTileBytes);
          v_part(step, kTileBytes, bar);
        }
        __syncwarp();
      };
      auto wait_flag = [&](int f) {
        flag_wait(flags + f);
      };
      auto store_out = [&](int tile, int w) {
        mbar_spin(bars + kBarStaged + 8 * w, tile & 1);
        asm volatile("fence.proxy.async.shared::cta;" ::: "memory");
        if (elect_one()) {
          const int row = (tile * 8 + grp) * kS + mt * 128 + w * 64;
#pragma unroll
          for (int c = 0; c < 3; c++)
            tma_store_2d(&tmo, sbase + kSmemV + w * kTileBytes + kTileBytes / 2 + c * 8192, c * 64, row);
          asm volatile("cp.async.bulk.commit_group;" ::: "memory");
        }
        __syncwarp();
      };
      auto reload_v = [&](int w, int step, uint32_t bar) {
        asm volatile("cp.async.bulk.wait_group.read 0;" ::: "memory");
        if (elect_one())
          bulk_load(sbase + kSmemV + w * kTileBytes + kTileBytes / 2, image(step, kTileBytes + kTileBytes / 2), kTileBytes / 2, bar);
        __syncwarp();
      };
      int pf = 3;
      uint32_t pf_at = unit_row(pf, grp, mt) * (kD * 4);
      auto prefetch_next = [&]() {
        const uint32_t at = pf_at;
        pf++;
        pf_at += (pf & 15) ? kBN * kD * 4 : (kBN + 7 * kS) * kD * 4;
        if (elect_one()) {
          prefetch_bulk((const uint8_t*)p.qv + at, 6144);
          if (pf < own) prefetch_bulk((const uint8_t*)p.qk + pf_at, 6144);
        }
        __syncwarp();
      };
      const uint8_t* prob = p.prob + (size_t)(blockIdx.x * kProbBytes);
      const int poll_step = (own - 3) | 1;
      auto load_p = [&](uint32_t dst, int q, uint32_t bar) {
        bulk_load(dst - rank * (kChunkBytes / 2), prob + kProbData + q * kChunkBytes, kChunkBytes, bar);
      };
      wait_flag(1);
      load_k01(1);
#pragma unroll 1
      for (int s = 0;; s++) {
        const bool newq = (s & 15) == 15;
        if (newq) {
          mbar_spin(bars + kBarEmptyQ, (s >> 4) & 1);
          if (elect_one()) load_q((s >> 4) + 1, 0);
          __syncwarp();
        }
        mbar_spin(bars + kBarEmptyK0, s & 1);
        load_k2(s + 1);
        if (s == 0) {
          if (elect_one()) {
            mbar_expect_tx(bars + kBarFullV, kTileBytes / 2);
            mbar_expect_tx(bars + kBarFullV2, kTileBytes / 2);
            v_part(0, kTileBytes / 2, bars + kBarFullV);
            bulk_load_mc(sbase + kSmemV + kTileBytes / 2 + rank * (kTileBytes / 4),
                         image(0, kTileBytes + kTileBytes / 2 + rank * (kTileBytes / 4)), kTileBytes / 4,
                         bars + kBarFullV2);
          }
          __syncwarp();
          prefetch_next();
        }
        const bool tile_end = (s & 15) == 0 && s > 0;
        if (tile_end) {
          store_out((s >> 4) - 1, 0);
          reload_v(0, s, bars + kBarFullV2);
        }
        const int pf_end = min(s + kLead + 2 + (s >= own - 7), kSteps - 1);
        if (pf < pf_end) prefetch_next();
        if (newq) {
          mbar_spin(bars + kBarEmptyQ + 8, (s >> 4) & 1);
          if (elect_one()) load_q((s >> 4) + 1, 1);
          __syncwarp();
        }
        if (s & 1) {
          uint32_t f = grp * kFlagsPerGroup + s + 2;
          if (lane == 31 && s == kStatStep) f = kFlagStats + grp;
          if (lane == 31 && s == poll_step) f = kFlagHelper + grp;
          f *= 4;
          asm("" : "+r"(f));
          flag_wait((const unsigned*)((const uint8_t*)p.flags + f));
        }
        if (s == poll_step && elect_one()) prefetch_bulk(prob, kProbData + tail * 2 * kChunkBytes);
        __syncwarp();
        mbar_spin(bars + kBarEmptyK12 + 8 * (s & 1), (s >> 1) & 1);
        if (s + 2 < own) {
          load_k01(s + 2);
        } else {
          const uint32_t d0 = next_slot(), d1 = next_slot();
          if (elect_one()) {
            mbar_expect_tx(bars + kBarUnits, 2 * kChunkBytes + 512);
            bulk_load(bars + kOffK, prob, 512, bars + kBarUnits);
            load_p(d0, 0, bars + kBarUnits);
            load_p(d1, 1, bars + kBarUnits);
          }
          __syncwarp();
        }
        mbar_spin(bars + kBarEmptyV + 8 * ((s + 1) & 1), (((s + 1) >> 1) & 1) ^ 1);
        if (newq || tile_end) {
          const uint32_t bar = bars + kBarFullV + 8 * ((s + 1) & 1);
          if (elect_one()) {
            mbar_expect_tx(bar, newq ? kTileBytes / 2 : kTileBytes);
            if (newq) mbar_expect_tx(bars + kBarFullV2, kTileBytes / 2);
            v_part(s + 1, kTileBytes / 2, bar);
          }
          __syncwarp();
          if (tile_end) {
            store_out((s >> 4) - 1, 1);
            reload_v(1, s + 1, bar);
          }
        } else {
          load_vt(s + 1);
        }
        if ((s & 15) == kStatStep && s < kSteps - 16) {
          uint4 x;
          asm volatile("ld.global.L1::no_allocate.v4.u32 {%0, %1, %2, %3}, [%4];"
                       : "=r"(x.x), "=r"(x.y), "=r"(x.z), "=r"(x.w)
                       : "l"(p.prob + (kHeadStats + (((s >> 4) + 1) * 8 + grp) * 512 + lane * 16))
                       : "memory");
          stat_keep(x, (s >> 4) + 1, lane, bars);
          __syncwarp();
        }
        asm volatile("st.volatile.shared.u32 [%0], %1;" ::"r"(bars + kProgress), "r"(s + 1) : "memory");
        if (pf <= pf_end && !tile_end) prefetch_next();
        if (s < kSteps - 16) {
          if ((s & 12) == 8) {
            const uint8_t* qn = (const uint8_t*)(p.q + (size_t)((((s >> 4) + 1) * 8 + grp) * kS + mt * 128) * kD);
            if (elect_one()) prefetch_bulk(qn + (s & 3) * 12288, 12288);
            __syncwarp();
          }
        }
        if (s == own - 2) break;
      }
      wait_flag(kSteps - 1);
      uint32_t vw = pick(tail, kPlacesV<1>, kPlacesV<2>, kPlacesV<3>);
      int q = 2;
#pragma unroll 1
      for (int i = 0;; i++) {
        vw >>= 8;
        const uint32_t bar = bars + (vw >> 1 & 0x78);
        mbar_spin(i == 0 ? bars + kBarEmptyK12 + 8 * ((own - 1) & 1) : bar + (kBarEmptyV - kBarFullV),
                  (i == 0 ? own - 1 : (vw ^ 4) >> 1) >> 1 & 1);
        if (i == 1) mbar_spin(bars + kBarFullQ, 0);
        if (elect_one()) {
          mbar_expect_tx(bar, kTileBytes);
          bulk_load_mc(sbase + (vw & 11) * 16384 + rank * (kTileBytes / 2), image(own + i, rank * (kTileBytes / 2)),
                       kTileBytes / 2, bar);
        }
        __syncwarp();
#pragma unroll 1
        for (; q < min(2 * i + 3, 2 * tail); q++) {
          const uint32_t d = next_slot();
          const uint32_t pb = bars + ((kBarCodes | kBarParams << 8 | (kBarFullQ + 8) << 16 | kBarFullQ2 << 24) >> (8 * q - 16) & 255);
          if (elect_one()) {
            mbar_expect_tx(pb, kChunkBytes);
            load_p(d, q, pb);
          }
          __syncwarp();
        }
        if (i == tail - 1) break;
      }
      unsigned done = 0;
      if (lane == 0)
        asm volatile("atom.global.inc.u32 %0, [%1], %2;" : "=r"(done) : "l"(p.flags + kFlagDone), "n"(kOwners - 1) : "memory");
      if (__shfl_sync(0xffffffffu, done, 0) == kOwners - 1) {
#pragma unroll
        for (int j = 0; j < 8 * kFlagsPerGroup / 128; j++) ((uint4*)p.flags)[j * 32 + lane] = make_uint4(0, 0, 0, 0);
        if (lane < 4) ((uint4*)p.flags)[kFlagHelper / 4 + lane] = make_uint4(0, 0, 0, 0);
      }
      __syncwarp();
      cluster_arrive();
#pragma unroll 1
      for (int j = 0; j < 6; j++) {
        const int w = (j + 1) >> 2;
        mbar_spin(bars + kBarTail + 8 * j, 0);
        asm volatile("fence.proxy.async.shared::cta;" ::: "memory");
        if (elect_one())
          tma_store_2d(&tmo, sbase + tail_stage + j * 8192, (j - 3 * w) * 64,
                       ((kWaves - 1) * 8 + grp) * kS + mt * 128 + w * 64);
        __syncwarp();
      }
      if (elect_one()) asm volatile("cp.async.bulk.commit_group;\ncp.async.bulk.wait_group.read 0;" ::: "memory");

    } else {
      const uint32_t t = threadIdx.x - 288;
      auto throttle = [&](int i) {
#pragma unroll 1
        for (int n = 0; n < 100000; n++) {
          int prog;
          asm volatile("ld.volatile.shared.u32 %0, [%1];" : "=r"(prog) : "r"(bars + kProgress) : "memory");
          if (__all_sync(0xffffffffu, i <= prog + kLead)) break;
          __nanosleep(200);
        }
      };
      asm volatile("bar.sync 3, 192;" ::: "memory");
      publish(p, 1, grp, 1);
      Unit v, k;
      load_unit<false>(p, unit_row(3, grp, mt), t, k);
      load_unit<true>(p, unit_row(2, grp, mt), t, v);
#pragma unroll 1
      for (int i = 2; i < kSteps; i++) {
        throttle(i - (i >= own));
        if (i + 1 < own) store_k(unit_dst<false>(p, i + 1, grp, mt, t), ((i + 1) >> 4) & 1, t, k, bars, codes_are_bytes(k));
        load_unit<false>(p, unit_row(min(i + 2, own - 1), grp, mt), t, k);
        store_v_any(unit_dst<true>(p, i, grp, mt, t, own), i, v, bars);
        if (i & 1) {
          if (warp == 9) {
            asm volatile("bar.sync %0, 96;" ::"r"(7 + (i & 2)) : "memory");
            publish(p, i, grp, 3);
          } else {
            asm volatile("bar.arrive %0, 96;" ::"r"(7 + (i & 2)) : "memory");
          }
        }
        load_unit<true>(p, unit_row(min(i + 1, kSteps - 1), grp, mt), t, v);
      }
    }
  } else {
    asm volatile("setmaxnreg.inc.sync.aligned.u32 224;");
    const int wg = warp >> 2;
    float S[64], O[96];
    uint32_t P[32];
    float m0 = 0.f, m1 = 0.f, l0 = 0.f, l1 = 0.f, h0 = 0.f, h1 = 0.f;
    bool shifted = false;
    auto release = [&](uint32_t bar) {
      if (lane < 2) mbar_arrive_cluster(bar, lane);
    };
    auto stage_o = [&](uint32_t stage, float f0, float f1, int c_lo, int c_hi) {
      const uint32_t addr = stage + ((warp & 3) * 16 + (lane & 15)) * 128 + (((lane >> 4) ^ (lane & 7)) << 4);
#pragma unroll
      for (int j = 4 * c_lo; j < 4 * c_hi; j++) {
        float* o = O + 8 * j;
#pragma unroll
        for (int i = 0; i < 8; i++) o[i] = (i & 2) ? fmaf(o[i], f1, h1) : fmaf(o[i], f0, h0);
        asm volatile("stmatrix.sync.aligned.m8n8.x4.shared.b16 [%0], {%1, %2, %3, %4};" ::"r"(
                         (addr ^ ((j & 3) * 32)) + (j >> 2) * 8192),
                     "r"(pack_bf16(o[0], o[1])), "r"(pack_bf16(o[2], o[3])), "r"(pack_bf16(o[4], o[5])),
                     "r"(pack_bf16(o[6], o[7]))
                     : "memory");
      }
    };
    auto staged = [&]() {
      __syncwarp();
      if (lane == 0) mbar_arrive_local(bars + kBarStaged + 8 * wg);
    };
    float sc0 = 1.f, sc1 = 1.f;
    auto quad_sum = [&](float x) {
      x += __shfl_xor_sync(0xffffffffu, x, 1);
      return x + __shfl_xor_sync(0xffffffffu, x, 2);
    };
    auto finish_l = [&](int wave, float& i0, float& i1) {
      const uint4 vp = lds128(bars + kParV + wave * 32);
      const float a = quad_sum(l0), b = quad_sum(l1);
      i0 = __uint_as_float(vp.z) * rcp(a);
      i1 = __uint_as_float(vp.z) * rcp(b);
      h0 = (a - 2.f * quad_sum(h0)) * i0 * __uint_as_float(vp.y);
      h1 = (b - 2.f * quad_sum(h1)) * i1 * __uint_as_float(vp.y);
    };
    auto issue_qk = [&](int s, int slot0) {
      const uint32_t kb = desc_lo(sbase + kSmemK, 16);
      const uint32_t qb = desc_lo(sbase + kSmemQ, 16) + wg * 1536;
#pragma unroll
      for (int c = 0; c < 3; c++) {
        const int slot = slot0 + c >= 5 ? slot0 + c - 5 : slot0 + c;
        if (c == 2) {
          mbar_wait(bars + kBarFullK2, s & 1);
          if ((s & 15) == 0) mbar_wait(bars + kBarFullQ2 + 8 * wg, (s >> 4) & 1);
        }
#pragma unroll
        for (int kk = 0; kk < 4; kk++)
          wgmma_ss_n128(S, desc64<1024>(qb + c * 512 + kk * 2), desc64<1024>(kb + slot * 1024 + kk * 2),
                        c + kk > 0);
        if (c != 1) wg_commit();
      }
    };
    auto issue_pv = [&](int s) {
      const uint32_t vb = desc_lo(sbase + kSmemV, 1024) + (s & 1) * (kTileBytes >> 4);
      const int acc = (s & 15) != 0;
      auto run = [&](int lo, int hi, int acc0) {
#pragma unroll
        for (int kk = lo; kk < hi; kk++)
          wgmma_rs_n192t(O, P[kk * 4], P[kk * 4 + 1], P[kk * 4 + 2], P[kk * 4 + 3], desc64<3072>(vb + kk * 384),
                         kk > 0 ? 1 : acc0);
      };
      if (acc) {
        wg_fence();
        run(0, 8, 1);
        wg_commit();
      } else {
        wg_fence();
        run(0, 4, 0);
        mbar_wait(bars + kBarFullV2, (s >> 4) & 1);
        wg_fence();
        run(4, 8, 1);
        wg_commit();
      }
    };
    auto shift = [&](int lo, float d0, float d1) {
#pragma unroll
      for (int i = lo; i < 64; i += 4) {
        S[i] -= d0;
        S[i + 1] -= d0;
        S[i + 2] -= d1;
        S[i + 3] -= d1;
      }
    };
    auto unsafe = [&](int lo, int hi, bool first) {
      int a0 = 0, a1 = 0, b0 = 0, b1 = 0;
#pragma unroll
      for (int i = lo; i < hi; i += 8) {
        a0 = __vimax3_s32(a0, __float_as_int(S[i]), __float_as_int(S[i + 1]));
        a1 = __vimax3_s32(a1, __float_as_int(S[i + 2]), __float_as_int(S[i + 3]));
        b0 = __vimax3_s32(b0, __float_as_int(S[i + 4]), __float_as_int(S[i + 5]));
        b1 = __vimax3_s32(b1, __float_as_int(S[i + 6]), __float_as_int(S[i + 7]));
      }
      bool bad = __vimax3_s32(max(a0, b0), a1, b1) > __float_as_int(kLazyAbove);
      if (first) {
        uint32_t u0 = ~0u, u1 = ~0u;
#pragma unroll
        for (int i = 0; i < 16; i += 4) {
          u0 = __vimin3_u32(u0, __float_as_uint(S[i]), __float_as_uint(S[i + 1]));
          u1 = __vimin3_u32(u1, __float_as_uint(S[i + 2]), __float_as_uint(S[i + 3]));
        }
        bad |= max(u0, u1) >= __float_as_uint(-kLazyBelow);
      }
      return __any_sync(0xffffffffu, bad);
    };
    float e0, e1;
    auto use_true_max = [&](int lo, bool first, bool boundary, float& f0, float& f1) {
      float d0 = S[lo], d1 = S[lo + 2];
#pragma unroll
      for (int i = lo; i < 64; i += 4) {
        d0 = fmaxf(d0, fmaxf(S[i], S[i + 1]));
        d1 = fmaxf(d1, fmaxf(S[i + 2], S[i + 3]));
      }
      d0 = fmaxf(d0, __shfl_xor_sync(0xffffffffu, d0, 1));
      d1 = fmaxf(d1, __shfl_xor_sync(0xffffffffu, d1, 1));
      d0 = fmaxf(d0, __shfl_xor_sync(0xffffffffu, d0, 2));
      d1 = fmaxf(d1, __shfl_xor_sync(0xffffffffu, d1, 2));
      if (!first) {
        d0 = fmaxf(d0, 0.f);
        d1 = fmaxf(d1, 0.f);
        f0 = ex2(-d0);
        f1 = ex2(-d1);
        l0 *= f0;
        l1 *= f1;
        if (!boundary) {
          h0 *= f0;
          h1 *= f1;
        }
#pragma unroll
        for (int i = 0; i < lo; i++) S[i] *= (i & 2) ? f1 : f0;
      }
      if (lo > 0) shift(lo, d0, d1);
      e0 = d0;
      e1 = d1;
      m0 += d0;
      m1 += d1;
      shifted = true;
    };
    auto exps = [&](int lo, int hi) {
#pragma unroll
      for (int i = lo; i < hi; i += 4) {
        S[i] = ex2(S[i]);
        S[i + 1] = ex2(S[i + 1]);
        S[i + 2] = ex2(S[i + 2]);
        S[i + 3] = ex2(S[i + 3]);
        l0 += S[i] + S[i + 1];
        l1 += S[i + 2] + S[i + 3];
      }
    };
    auto to_p = [&]() {
#pragma unroll
      for (int j = 0; j < 32; j++) P[j] = pack_f16(S[2 * j], S[2 * j + 1]);
    };
    auto scale_o = [&](float f0, float f1) {
#pragma unroll
      for (int i = 0; i < 96; i += 4) {
        O[i] *= f0;
        O[i + 1] *= f0;
        O[i + 2] *= f1;
        O[i + 3] *= f1;
      }
    };
#pragma unroll
    for (int i = 0; i < 96; i++) asm volatile("" : "=f"(O[i]));
#pragma unroll
    for (int i = 0; i < 32; i++) asm volatile("" : "=r"(P[i]));
    if (threadIdx.x == 128) asm volatile("prefetch.tensormap [%0];" ::"l"(&tmo) : "memory");
    if (wg == 1) bar_arrive(1);
    int slot0 = 2;
#pragma unroll 1
    for (int s = 0;; s++) {
      const bool boundary = (s & 15) == 0;
      slot0 = slot0 >= 2 ? slot0 - 2 : slot0 + 3;
      if (boundary) mbar_wait(bars + kBarFullQ + 8 * wg, (s >> 4) & 1);
      mbar_wait(bars + kBarFullK01 + 8 * (s & 1), (s >> 1) & 1);
      bar_sync(1 + wg);
      pin(P);
      pin(O);
      wg_fence();
      issue_qk(s, slot0);
      mbar_wait(bars + kBarFullV + 8 * ((s - 1) & 1), ((s - 1) >> 1) & 1);
      wg_wait<1>();
      release(bars + kBarEmptyK0);
      if (s > 0) issue_pv(s - 1);
      else wg_commit();
      bar_arrive(2 - wg);
      wg_wait<1>();
      pin(S);
      release(bars + kBarEmptyK12 + 8 * (s & 1));
      if ((s & 15) == 15 && lane == 0) mbar_arrive_local(bars + kBarEmptyQ + 8 * wg);
      bool rescale = false;
      e0 = m0;
      e1 = m1;
#pragma unroll 1
      for (;;) {
        if (shifted) shift(0, e0, e1);
        if (rescale || !unsafe(0, kExpSplit, boundary)) break;
        use_true_max(0, boundary, boundary, sc0, sc1);
        rescale = true;
      }
      const bool late = unsafe(kExpSplit, 64, false);
      exps(0, kExpSplit);
      pin(S);
      asm volatile("st.volatile.shared.f32 [%0], %1;" ::"r"(bars + kDummy), "f"(l0 + l1) : "memory");
      wg_wait<0>();
      pin(O);
      pin(P);
      if (s > 0) {
        release(bars + kBarEmptyV + 8 * ((s - 1) & 1));
        if (((s + wg) & 15) == 0 && lane == 0) mbar_arrive_local(bars + kBarStage + 8 * (1 - wg));
      }
      if (late) {
        float f0, f1;
        use_true_max(kExpSplit, false, boundary, f0, f1);
        if (!boundary) {
          sc0 = f0;
          sc1 = f1;
          rescale = true;
        }
      }
      if (boundary && s > 0) {
        mbar_spin(bars + kBarStage + 8 * wg, ((s >> 4) - 1) & 1);
        stage_o(sbase + kSmemV + wg * kTileBytes + kTileBytes / 2, sc0, sc1, 0, 3);
        staged();
      } else if (rescale && s > 0) {
        scale_o(sc0, sc1);
      }
      pin(S);
      exps(kExpSplit, 64);
      to_p();
      if ((s & 15) == 7) {
        h0 = l0;
        h1 = l1;
      }
      if ((s & 15) == 15) {
        finish_l(s >> 4, sc0, sc1);
        m0 = m1 = l0 = l1 = 0.f;
        shifted = false;
      }
      if (s == own - 1) break;
    }
    uint32_t vw = pick(tail, kPlacesV<1>, kPlacesV<2>, kPlacesV<3>);
    uint32_t pw = wg ? pick(tail, kPlacesP<1, 1>, kPlacesP<2, 1>, kPlacesP<3, 1>)
                     : pick(tail, kPlacesP<1, 0>, kPlacesP<2, 0>, kPlacesP<3, 0>);
    auto next_v = [&]() {
      mbar_spin(bars + (vw >> 1 & 0x78), vw >> 2 & 1);
      const uint32_t vb = desc_lo(sbase, 1024) + (vw & 11) * 1024;
      vw >>= 8;
      return vb;
    };
    bool rescale = false;
    const float4* extra = (const float4*)(p.prob + (size_t)(blockIdx.x * kProbBytes + kProbExtra + (threadIdx.x >> 2) * 16));
    auto next_p = [&]() {
      mbar_spin(bars + (pw >> 1 & 0xF8), pw >> 3 & 1);
      const uint32_t a = sbase + (pw & 7) * 16384 + (threadIdx.x & 127) * 16;
      pw >>= 10;
      if (rescale) {
        const float4 b = __ldcg(extra);
        extra += 64;
        scale_p(a, ex2(b.x - m0), ex2(b.y - m1));
      }
      return a;
    };
    auto take = [&](uint32_t (&A)[32], uint32_t a) {
#pragma unroll
      for (int i = 0; i < 8; i++) {
        const uint4 x = lds128v(a + i * 2048);
        A[4 * i] = x.x, A[4 * i + 1] = x.y, A[4 * i + 2] = x.z, A[4 * i + 3] = x.w;
      }
      pin(A);
    };
    float f0 = 1.f, f1 = 1.f;
    uint32_t pa;
#pragma unroll 1
    for (int x = 0;; x++) {
      const uint32_t vb = next_v();
      bar_sync(1 + wg);
      pin(P);
      pin(O);
      wg_fence();
#pragma unroll
      for (int kk = 0; kk < 8; kk++)
        wgmma_rs_n192t(O, P[kk * 4], P[kk * 4 + 1], P[kk * 4 + 2], P[kk * 4 + 3], desc64<3072>(vb + kk * 384), 1);
      wg_commit();
      if (x < tail - 1) bar_arrive(2 - wg);
      if (x == 0) {
        mbar_spin(bars + kBarUnits, 1);
        const uint2 r = lds64(bars + kOffK + (threadIdx.x >> 2) * 8);
        float r0 = __uint_as_float(r.x), r1 = __uint_as_float(r.y);
        rescale = shifted || __any_sync(0xffffffffu, r0 < 0.f);
        if (rescale) {
          float n0 = m0, n1 = m1;
          r0 = r1 = 0.f;
#pragma unroll 1
          for (int j = 0;; j++) {
            const float4 b = __ldcg(extra + j * 64);
            const float x0 = fmaxf(n0, b.x), x1 = fmaxf(n1, b.y);
            r0 = r0 * ex2(n0 - x0) + b.z * ex2(b.x - x0);
            r1 = r1 * ex2(n1 - x1) + b.w * ex2(b.y - x1);
            n0 = x0;
            n1 = x1;
            if (j == tail - 1) break;
          }
          f0 = ex2(m0 - n0);
          f1 = ex2(m1 - n1);
          l0 *= f0;
          l1 *= f1;
          h0 *= f0;
          h1 *= f1;
          m0 = n0;
          m1 = n1;
        }
        l0 += r0;
        l1 += r1;
        finish_l(kWaves - 1, sc0, sc1);
        asm volatile("st.volatile.shared.f32 [%0], %1;" ::"r"(bars + kDummy), "f"(h0 + h1) : "memory");
      }
      pa = next_p();
      if (x == tail - 1) break;
      wg_wait<0>();
      pin(O);
      pin(P);
      if (rescale && x == 0) {
        scale_o(f0, f1);
        f0 = f1 = 1.f;
      }
      take(P, pa);
      release(bars + kBarEmptyV + 8 * ((own - 1 + x) & 1));
    }
    cluster_arrive();
    uint32_t R[32];
    take(R, pa);
    const uint32_t v_last = next_v();
    float T0[32], T1[32];
    auto tail_pv = [&](float (&T)[32], int c) {
      const uint32_t vb = v_last + c * 64;
      wg_fence();
#pragma unroll
      for (int kk = 0; kk < 8; kk++)
        wgmma_rs_n64t(T, R[kk * 4], R[kk * 4 + 1], R[kk * 4 + 2], R[kk * 4 + 3], desc64<3072>(vb + kk * 384), kk > 0);
      wg_commit();
    };
    uint32_t X[16];
    auto tail_pack = [&](float (&T)[32], int c) {
      pin(T);
#pragma unroll
      for (int i = 0; i < 16; i++) {
        const float f = (i & 1) ? sc1 : sc0;
        X[i] = pack_bf16(fmaf(T[2 * i], f, O[32 * c + 2 * i]), fmaf(T[2 * i + 1], f, O[32 * c + 2 * i + 1]));
      }
      pin(X);
    };
    auto tail_store = [&](int c) {
      const uint32_t addr = sbase + tail_stage + wg * (kTileBytes / 2) + c * 8192 +
                            ((warp & 3) * 16 + (lane & 15)) * 128 + (((lane >> 4) ^ (lane & 7)) << 4);
#pragma unroll
      for (int j = 0; j < 4; j++)
        asm volatile("stmatrix.sync.aligned.m8n8.x4.shared.b16 [%0], {%1, %2, %3, %4};" ::"r"(addr ^ (j * 32)), "r"(X[4 * j]),
                     "r"(X[4 * j + 1]), "r"(X[4 * j + 2]), "r"(X[4 * j + 3])
                     : "memory");
      __syncwarp();
      if (lane == 0) mbar_arrive_local(bars + kBarTail + 24 * wg + 8 * c);
    };
    tail_pv(T0, 0);
    f0 *= sc0;
    f1 *= sc1;
    wg_wait<1>();
    pin(P);
    auto prescale = [&](int c) {
      pin(O);
#pragma unroll
      for (int i = 32 * c; i < 32 * c + 32; i++) O[i] = (i & 2) ? fmaf(O[i], f1, h1) : fmaf(O[i], f0, h0);
      pin(O);
      mbar_spin(bars + kBarEmptyV + 8, 0);
    };
    prescale(0);
    tail_pv(T1, 1);
    if (wg == 0) bar_arrive(2);
    wg_wait<1>();
    tail_pack(T0, 0);
    tail_store(0);
    tail_pv(T0, 2);
    prescale(1);
    wg_wait<1>();
    tail_pack(T1, 1);
    tail_store(1);
    prescale(2);
    wg_wait<0>();
    tail_pack(T0, 2);
    tail_store(2);
    cluster_wait();
  }
}

}

extern "C" void kernel_launch(void* const* d_in, const int* in_sizes, int n_in, void* d_out, int out_size) {
  static CUtensorMap tmq, tmo;
  static const void *tm_q = nullptr, *tm_o = nullptr;
  static void *scratch, *flags, *prob;
  if (tm_q != d_in[0] || tm_o != d_out) {
    typedef CUresult (*EncodeFn)(CUtensorMap*, CUtensorMapDataType, cuuint32_t, void*, const cuuint64_t*,
                                 const cuuint64_t*, const cuuint32_t*, const cuuint32_t*, CUtensorMapInterleave,
                                 CUtensorMapSwizzle, CUtensorMapL2promotion, CUtensorMapFloatOOBfill);
    void* fn = nullptr;
    cudaDriverEntryPointQueryResult qr;
    cudaGetDriverEntryPoint("cuTensorMapEncodeTiled", &fn, cudaEnableDefault, &qr);
    cuuint64_t dims[2] = {(cuuint64_t)kD, (cuuint64_t)kH * kS};
    cuuint64_t strides[1] = {(cuuint64_t)kD * 2};
    cuuint32_t box[2] = {64, 64};
    cuuint32_t estr[2] = {1, 1};
    ((EncodeFn)fn)(&tmq, CU_TENSOR_MAP_DATA_TYPE_BFLOAT16, 2, d_in[0], dims, strides, box, estr,
                   CU_TENSOR_MAP_INTERLEAVE_NONE, CU_TENSOR_MAP_SWIZZLE_128B, CU_TENSOR_MAP_L2_PROMOTION_L2_128B,
                   CU_TENSOR_MAP_FLOAT_OOB_FILL_NONE);
    ((EncodeFn)fn)(&tmo, CU_TENSOR_MAP_DATA_TYPE_BFLOAT16, 2, d_out, dims, strides, box, estr,
                   CU_TENSOR_MAP_INTERLEAVE_NONE, CU_TENSOR_MAP_SWIZZLE_128B, CU_TENSOR_MAP_L2_PROMOTION_NONE,
                   CU_TENSOR_MAP_FLOAT_OOB_FILL_NONE);
    cudaFuncSetAttribute(attn_kernel, cudaFuncAttributeMaxDynamicSharedMemorySize, kSmemTotal);
    cudaGetSymbolAddress(&scratch, g_scratch);
    cudaGetSymbolAddress(&flags, g_flags);
    cudaGetSymbolAddress(&prob, g_prob);
    tm_q = d_in[0];
    tm_o = d_out;
  }
  Params p;
  p.q = (const __nv_bfloat16*)d_in[0];
  p.qk = (const int*)d_in[1];
  p.qv = (const int*)d_in[2];
  p.ks = (const __nv_bfloat16*)d_in[3];
  p.kz = (const __nv_bfloat16*)d_in[4];
  p.vs = (const __nv_bfloat16*)d_in[5];
  p.vz = (const __nv_bfloat16*)d_in[6];
  p.scratch = (uint8_t*)scratch;
  p.flags = (unsigned*)flags;
  p.prob = (uint8_t*)prob;
  attn_kernel<<<kOwners + kHelpers, 384, kSmemTotal>>>(p, tmq, tmo);
}
```

```cpp
#include <cuda_runtime.h>
#include <cuda_bf16.h>
#include <cuda.h>
#include <math.h>
#include <stdint.h>

namespace {

constexpr int kH = 32, kS = 2048, kD = 192;
constexpr int kGroupTok = 64;
constexpr int kBN = 128;
constexpr int kNBlk = kS / kBN;
constexpr int kWaves = 4;
constexpr int kSteps = kWaves * kNBlk;
constexpr int kTileBytes = kBN * kD * 2;
constexpr int kOwners = 128, kHelpers = 4;
constexpr uint32_t kTails = 0x33222112u;
constexpr uint32_t kJobs = 0x30214567u;
constexpr int kMaxTail = 3;
__device__ __forceinline__ int tail_blocks(int grp) { return (kTails >> (4 * grp)) & 3; }
constexpr uint32_t kHelperDelay = 42000, kHelperPrepare = 12000;
constexpr int kProbExtra = 512, kProbData = 4096, kProbBytes = kProbData + 2 * kMaxTail * 16384;
constexpr int kFlagTarget = 48;
constexpr int kFlagsPerGroup = kSteps;
constexpr float kLazyAbove = 15.f, kLazyBelow = 11.f;
constexpr int kLead = 3;
constexpr int kRing = 2 * kLead + 2;
static_assert((kRing & (kRing - 1)) == 0, "power of two");
constexpr int kBarPolls = 1 << 13, kFlagPolls = 1 << 16;

constexpr uint64_t pack_delays(int a, int b, int c, int d, int e, int f, int g, int h) {
  const int t[8] = {a, b, c, d, e, f, g, h};
  uint64_t w = 0;
  for (int i = 0; i < 8; i++) w |= (uint64_t)((t[i] + 16) / 32) << 8 * i;
  return w;
}
constexpr uint64_t kCodeDelays = pack_delays(500, 0, 0, 750, 1000, 1250, 1500, 1750), kQueryDelays = pack_delays(3340, 1900, 2600, 3860, 4380, 4900, 5420, 5940);
constexpr int kStatStep = 9;
static_assert(kStatStep + kLead < 15, "the first block of a head is expanded after its statistics have arrived");
constexpr uint32_t kOffsetFactor = 0x3EA03EA0u;
constexpr int kExpSplit = 32;
constexpr int kChunkBytes = kBN * 128;
constexpr int kSmemQ = 0;
constexpr int kSmemK = kTileBytes;
constexpr int kSmemV = kSmemK + 5 * kChunkBytes;
constexpr int kSmemBar = kSmemV + 2 * kTileBytes;
constexpr int kOffK = 256, kParV = kOffK + 2 * kD * 2, kBarBytes = kParV + 128;
constexpr int kSmemTotal = kSmemBar + kBarBytes + 1024;

constexpr int kBarFullK01 = 0, kBarFullV = 16, kBarEmptyK12 = 32, kBarEmptyV = 48, kBarFullQ = 64, kBarEmptyQ = 80,
              kBarFullK2 = 96, kBarEmptyK0 = 104, kBarStage = 112, kBarStaged = 128, kBarFullV2 = 144,
              kBarFullQ2 = 152, kBarCodes = 168, kBarTail = 176, kProgress = 224, kDummy = 228, kBarParams = 232,
              kBarUnits = 240;

constexpr uint32_t v_places(int n) {
  uint32_t w = (kSmemQ >> 14 | kBarFullQ << 1) << 8;
  for (int x = 0; x <= n; x += x ? 1 : 2) {
    const int v = kSteps - n + x - (x ? 2 : 1);
    w |= ((kSmemV + (v & 1) * kTileBytes) >> 14 | (v & 2) << 1 | (kBarFullV + 8 * (v & 1)) << 1) << 8 * x;
  }
  return w;
}
constexpr uint32_t p_places(int n, int wg) {
  constexpr int bar[6] = {kBarUnits, kBarUnits, kBarCodes, kBarParams, kBarFullQ + 8, kBarFullQ2};
  uint32_t w = 0;
  for (int j = 0; j < n; j++)
    w |= ((kSmemK >> 14) + (3 * (kSteps - n) + 2 * j + wg) % 5 | (j < 2) << 3 | bar[2 * j + wg] << 1) << 10 * j;
  return w;
}
template <int n> constexpr uint32_t kPlacesV = v_places(n);
template <int n, int wg> constexpr uint32_t kPlacesP = p_places(n, wg);
__device__ __forceinline__ uint32_t pick(int n, uint32_t a, uint32_t b, uint32_t c) { return n == 1 ? a : n == 2 ? b : c; }

__device__ __align__(1024) uint4 g_scratch[(size_t)8 * kRing * 2 * kTileBytes / 16];
constexpr int kFlagHelper = 8 * kFlagsPerGroup, kFlagStats = kFlagHelper + 8, kFlagDone = kFlagStats + 8;
__device__ __align__(16) unsigned g_flags[kFlagDone + 1];
constexpr int kHelperImages = kOwners * kProbBytes, kHeadStats = kHelperImages + 8 * kMaxTail * kTileBytes;
__device__ __align__(1024) uint4 g_prob[(kHeadStats + kH * 512) / 16];

__device__ __forceinline__ void wgmma_ss_n128(float (&d)[64], uint64_t da, uint64_t db, int scale_d) {
  asm volatile("{\n.reg .pred p;\nsetp.ne.b32 p, %66, 0;\n"
    "wgmma.mma_async.sync.aligned.m64n128k16.f32.bf16.bf16 "
    "{%0, %1, %2, %3, %4, %5, %6, %7, %8, %9, %10, %11, %12, %13, %14, %15, %16, %17, %18, %19, %20, %21, %22, %23, %24, %25, %26, %27, %28, %29, %30, %31, %32, %33, %34, %35, %36, %37, %38, %39, %40, %41, %42, %43, %44, %45, %46, %47, %48, %49, %50, %51, %52, %53, %54, %55, %56, %57, %58, %59, %60, %61, %62, %63}, %64, %65, p, 1, 1, 0, 0;\n}\n"
    : "+f"(d[0]), "+f"(d[1]), "+f"(d[2]), "+f"(d[3]), "+f"(d[4]), "+f"(d[5]), "+f"(d[6]), "+f"(d[7]), "+f"(d[8]), "+f"(d[9]), "+f"(d[10]), "+f"(d[11]), "+f"(d[12]), "+f"(d[13]), "+f"(d[14]), "+f"(d[15]), "+f"(d[16]), "+f"(d[17]), "+f"(d[18]), "+f"(d[19]), "+f"(d[20]), "+f"(d[21]), "+f"(d[22]), "+f"(d[23]), "+f"(d[24]), "+f"(d[25]), "+f"(d[26]), "+f"(d[27]), "+f"(d[28]), "+f"(d[29]), "+f"(d[30]), "+f"(d[31]), "+f"(d[32]), "+f"(d[33]), "+f"(d[34]), "+f"(d[35]), "+f"(d[36]), "+f"(d[37]), "+f"(d[38]), "+f"(d[39]), "+f"(d[40]), "+f"(d[41]), "+f"(d[42]), "+f"(d[43]), "+f"(d[44]), "+f"(d[45]), "+f"(d[46]), "+f"(d[47]), "+f"(d[48]), "+f"(d[49]), "+f"(d[50]), "+f"(d[51]), "+f"(d[52]), "+f"(d[53]), "+f"(d[54]), "+f"(d[55]), "+f"(d[56]), "+f"(d[57]), "+f"(d[58]), "+f"(d[59]), "+f"(d[60]), "+f"(d[61]), "+f"(d[62]), "+f"(d[63])
    : "l"(da), "l"(db), "r"(scale_d));
}
__device__ __forceinline__ void wgmma_new_n128(float (&d)[64], uint64_t da, uint64_t db) {
  asm volatile("{\n.reg .pred p;\nsetp.ne.b32 p, 0, 0;\n"
    "wgmma.mma_async.sync.aligned.m64n128k16.f32.bf16.bf16 "
    "{%0, %1, %2, %3, %4, %5, %6, %7, %8, %9, %10, %11, %12, %13, %14, %15, %16, %17, %18, %19, %20, %21, %22, %23, %24, %25, %26, %27, %28, %29, %30, %31, %32, %33, %34, %35, %36, %37, %38, %39, %40, %41, %42, %43, %44, %45, %46, %47, %48, %49, %50, %51, %52, %53, %54, %55, %56, %57, %58, %59, %60, %61, %62, %63}, %64, %65, p, 1, 1, 0, 0;\n}\n"
    : "=f"(d[0]), "=f"(d[1]), "=f"(d[2]), "=f"(d[3]), "=f"(d[4]), "=f"(d[5]), "=f"(d[6]), "=f"(d[7]), "=f"(d[8]), "=f"(d[9]), "=f"(d[10]), "=f"(d[11]), "=f"(d[12]), "=f"(d[13]), "=f"(d[14]), "=f"(d[15]), "=f"(d[16]), "=f"(d[17]), "=f"(d[18]), "=f"(d[19]), "=f"(d[20]), "=f"(d[21]), "=f"(d[22]), "=f"(d[23]), "=f"(d[24]), "=f"(d[25]), "=f"(d[26]), "=f"(d[27]), "=f"(d[28]), "=f"(d[29]), "=f"(d[30]), "=f"(d[31]), "=f"(d[32]), "=f"(d[33]), "=f"(d[34]), "=f"(d[35]), "=f"(d[36]), "=f"(d[37]), "=f"(d[38]), "=f"(d[39]), "=f"(d[40]), "=f"(d[41]), "=f"(d[42]), "=f"(d[43]), "=f"(d[44]), "=f"(d[45]), "=f"(d[46]), "=f"(d[47]), "=f"(d[48]), "=f"(d[49]), "=f"(d[50]), "=f"(d[51]), "=f"(d[52]), "=f"(d[53]), "=f"(d[54]), "=f"(d[55]), "=f"(d[56]), "=f"(d[57]), "=f"(d[58]), "=f"(d[59]), "=f"(d[60]), "=f"(d[61]), "=f"(d[62]), "=f"(d[63])
    : "l"(da), "l"(db));
}
__device__ __forceinline__ void wgmma_rs_n64t(float (&d)[32], uint32_t a0, uint32_t a1, uint32_t a2, uint32_t a3, uint64_t db, int scale_d) {
  asm volatile("{\n.reg .pred p;\nsetp.ne.b32 p, %37, 0;\n"
    "wgmma.mma_async.sync.aligned.m64n64k16.f32.f16.f16 "
    "{%0, %1, %2, %3, %4, %5, %6, %7, %8, %9, %10, %11, %12, %13, %14, %15, %16, %17, %18, %19, %20, %21, %22, %23, %24, %25, %26, %27, %28, %29, %30, %31}, {%32, %33, %34, %35}, %36, p, 1, 1, 1;\n}\n"
    : "+f"(d[0]), "+f"(d[1]), "+f"(d[2]), "+f"(d[3]), "+f"(d[4]), "+f"(d[5]), "+f"(d[6]), "+f"(d[7]), "+f"(d[8]), "+f"(d[9]), "+f"(d[10]), "+f"(d[11]), "+f"(d[12]), "+f"(d[13]), "+f"(d[14]), "+f"(d[15]), "+f"(d[16]), "+f"(d[17]), "+f"(d[18]), "+f"(d[19]), "+f"(d[20]), "+f"(d[21]), "+f"(d[22]), "+f"(d[23]), "+f"(d[24]), "+f"(d[25]), "+f"(d[26]), "+f"(d[27]), "+f"(d[28]), "+f"(d[29]), "+f"(d[30]), "+f"(d[31])
    : "r"(a0), "r"(a1), "r"(a2), "r"(a3), "l"(db), "r"(scale_d));
}
__device__ __forceinline__ void wgmma_rs_n192t(float (&d)[96], uint32_t a0, uint32_t a1, uint32_t a2, uint32_t a3, uint64_t db, int scale_d) {
  asm volatile("{\n.reg .pred p;\nsetp.ne.b32 p, %101, 0;\n"
    "wgmma.mma_async.sync.aligned.m64n192k16.f32.f16.f16 "
    "{%0, %1, %2, %3, %4, %5, %6, %7, %8, %9, %10, %11, %12, %13, %14, %15, %16, %17, %18, %19, %20, %21, %22, %23, %24, %25, %26, %27, %28, %29, %30, %31, %32, %33, %34, %35, %36, %37, %38, %39, %40, %41, %42, %43, %44, %45, %46, %47, %48, %49, %50, %51, %52, %53, %54, %55, %56, %57, %58, %59, %60, %61, %62, %63, %64, %65, %66, %67, %68, %69, %70, %71, %72, %73, %74, %75, %76, %77, %78, %79, %80, %81, %82, %83, %84, %85, %86, %87, %88, %89, %90, %91, %92, %93, %94, %95}, {%96, %97, %98, %99}, %100, p, 1, 1, 1;\n}\n"
    : "+f"(d[0]), "+f"(d[1]), "+f"(d[2]), "+f"(d[3]), "+f"(d[4]), "+f"(d[5]), "+f"(d[6]), "+f"(d[7]), "+f"(d[8]), "+f"(d[9]), "+f"(d[10]), "+f"(d[11]), "+f"(d[12]), "+f"(d[13]), "+f"(d[14]), "+f"(d[15]), "+f"(d[16]), "+f"(d[17]), "+f"(d[18]), "+f"(d[19]), "+f"(d[20]), "+f"(d[21]), "+f"(d[22]), "+f"(d[23]), "+f"(d[24]), "+f"(d[25]), "+f"(d[26]), "+f"(d[27]), "+f"(d[28]), "+f"(d[29]), "+f"(d[30]), "+f"(d[31]), "+f"(d[32]), "+f"(d[33]), "+f"(d[34]), "+f"(d[35]), "+f"(d[36]), "+f"(d[37]), "+f"(d[38]), "+f"(d[39]), "+f"(d[40]), "+f"(d[41]), "+f"(d[42]), "+f"(d[43]), "+f"(d[44]), "+f"(d[45]), "+f"(d[46]), "+f"(d[47]), "+f"(d[48]), "+f"(d[49]), "+f"(d[50]), "+f"(d[51]), "+f"(d[52]), "+f"(d[53]), "+f"(d[54]), "+f"(d[55]), "+f"(d[56]), "+f"(d[57]), "+f"(d[58]), "+f"(d[59]), "+f"(d[60]), "+f"(d[61]), "+f"(d[62]), "+f"(d[63]), "+f"(d[64]), "+f"(d[65]), "+f"(d[66]), "+f"(d[67]), "+f"(d[68]), "+f"(d[69]), "+f"(d[70]), "+f"(d[71]), "+f"(d[72]), "+f"(d[73]), "+f"(d[74]), "+f"(d[75]), "+f"(d[76]), "+f"(d[77]), "+f"(d[78]), "+f"(d[79]), "+f"(d[80]), "+f"(d[81]), "+f"(d[82]), "+f"(d[83]), "+f"(d[84]), "+f"(d[85]), "+f"(d[86]), "+f"(d[87]), "+f"(d[88]), "+f"(d[89]), "+f"(d[90]), "+f"(d[91]), "+f"(d[92]), "+f"(d[93]), "+f"(d[94]), "+f"(d[95])
    : "r"(a0), "r"(a1), "r"(a2), "r"(a3), "l"(db), "r"(scale_d));
}

__device__ __forceinline__ uint32_t desc_lo(uint32_t addr, uint32_t lbo) { return ((addr & 0x3FFFF) >> 4) | ((lbo >> 4) << 16); }
template <uint32_t SBO>
__device__ __forceinline__ uint64_t desc64(uint32_t lo) {
  uint64_t d;
  asm("mov.b64 %0, {%1, %2};" : "=l"(d) : "r"(lo), "n"((SBO >> 4) | (1u << 30)));
  return d;
}
__device__ __forceinline__ void wg_fence() { asm volatile("wgmma.fence.sync.aligned;" ::: "memory"); }
__device__ __forceinline__ void wg_commit() { asm volatile("wgmma.commit_group.sync.aligned;" ::: "memory"); }
template <int N>
__device__ __forceinline__ void wg_wait() { asm volatile("wgmma.wait_group.sync.aligned %0;" ::"n"(N) : "memory"); }
__device__ __forceinline__ void bar_sync(int id) { asm volatile("bar.sync %0, 256;" ::"r"(id) : "memory"); }
__device__ __forceinline__ void bar_arrive(int id) { asm volatile("bar.arrive %0, 256;" ::"r"(id) : "memory"); }

template <int N>
__device__ __forceinline__ void pin(float (&r)[N]) {
#pragma unroll
  for (int i = 0; i < N; i++) asm volatile("" : "+f"(r[i])::"memory");
}
template <int N>
__device__ __forceinline__ void pin(uint32_t (&r)[N]) {
#pragma unroll
  for (int i = 0; i < N; i++) asm volatile("" : "+r"(r[i])::"memory");
}

__device__ __forceinline__ void mbar_init(uint32_t bar, uint32_t count) {
  asm volatile("mbarrier.init.shared::cta.b64 [%0], %1;" ::"r"(bar), "r"(count) : "memory");
}
__device__ __forceinline__ void mbar_expect_tx(uint32_t bar, uint32_t bytes) {
  asm volatile("mbarrier.arrive.expect_tx.shared::cta.b64 _, [%0], %1;" ::"r"(bar), "r"(bytes) : "memory");
}
__device__ __forceinline__ void mbar_arrive_local(uint32_t bar) {
  asm volatile("mbarrier.arrive.shared::cta.b64 _, [%0];" ::"r"(bar) : "memory");
}
__device__ __forceinline__ void mbar_arrive_cluster(uint32_t bar, uint32_t cta) {
  asm volatile(
      "{\n.reg .b32 ra;\nmapa.shared::cluster.u32 ra, %0, %1;\n"
      "mbarrier.arrive.shared::cluster.b64 _, [ra];\n}" ::"r"(bar),
      "r"(cta)
      : "memory");
}
__device__ __forceinline__ bool mbar_try(uint32_t bar, uint32_t parity) {
  uint32_t ok;
  asm volatile(
      "{\n.reg .pred p;\nmbarrier.try_wait.parity.shared::cta.b64 p, [%1], %2;\nselp.u32 %0, 1, 0, p;\n}"
      : "=r"(ok)
      : "r"(bar), "r"(parity)
      : "memory");
  return ok;
}
__device__ __forceinline__ uint32_t now_clk() {
  uint32_t t;
  asm volatile("mov.u32 %0, %%clock;" : "=r"(t));
  return t;
}
__device__ __forceinline__ void mbar_wait(uint32_t bar, uint32_t parity) {
  if (mbar_try(bar, parity)) return;
#pragma unroll 1
  for (int n = now_clk() & 1; n < kBarPolls; n++)
    if (mbar_try(bar, parity)) break;
}
__device__ __forceinline__ void mbar_spin(uint32_t bar, uint32_t parity) {
#pragma unroll 1
  for (int n = 0; n < kBarPolls; n++)
    if (mbar_try(bar, parity)) break;
}
__device__ __forceinline__ bool elect_one() {
  uint32_t r;
  asm volatile("{\n.reg .pred p;\nelect.sync _|p, 0xffffffff;\nselp.u32 %0, 1, 0, p;\n}" : "=r"(r));
  return r;
}
__device__ __forceinline__ void bulk_load(uint32_t dst, const void* src, uint32_t bytes, uint32_t bar) {
  asm volatile("cp.async.bulk.shared::cluster.global.mbarrier::complete_tx::bytes [%0], [%1], %2, [%3];" ::"r"(dst),
               "l"(src), "r"(bytes), "r"(bar)
               : "memory");
}
__device__ __forceinline__ void bulk_copy_peer(uint32_t addr, uint32_t bytes, uint32_t bar, uint32_t cta) {
  asm volatile(
      "{\n.reg .b32 ra, rb;\nmapa.shared::cluster.u32 ra, %0, %3;\nmapa.shared::cluster.u32 rb, %2, %3;\n"
      "cp.async.bulk.shared::cluster.shared::cta.mbarrier::complete_tx::bytes [ra], [%0], %1, [rb];\n}" ::"r"(addr),
      "r"(bytes), "r"(bar), "r"(cta)
      : "memory");
}
__device__ __forceinline__ void bulk_load_mc(uint32_t dst, const void* src, uint32_t bytes, uint32_t bar) {
  asm volatile(
      "cp.async.bulk.shared::cluster.global.mbarrier::complete_tx::bytes.multicast::cluster [%0], [%1], %2, [%3], "
      "%4;" ::"r"(dst),
      "l"(src), "r"(bytes), "r"(bar), "h"((uint16_t)3)
      : "memory");
}
constexpr uint64_t kEvictFirst = 0x12F0000000000000ull;
__device__ __forceinline__ void tma_load_2d(uint32_t dst, const CUtensorMap* map, int c0, int c1, uint32_t bar) {
  asm volatile(
      "cp.async.bulk.tensor.2d.shared::cluster.global.mbarrier::complete_tx::bytes.L2::cache_hint [%0], [%1, {%3, %4}], "
      "[%2], %5;" ::"r"(dst),
      "l"(map), "r"(bar), "r"(c0), "r"(c1), "l"(kEvictFirst)
      : "memory");
}
__device__ __forceinline__ void tma_store_2d(const CUtensorMap* map, uint32_t src, int c0, int c1) {
  asm volatile("cp.async.bulk.tensor.2d.global.shared::cta.bulk_group [%0, {%2, %3}], [%1];" ::"l"(map), "r"(src),
               "r"(c0), "r"(c1)
               : "memory");
}
__device__ __forceinline__ void cluster_arrive() { asm volatile("barrier.cluster.arrive.relaxed;" ::: "memory"); }
__device__ __forceinline__ void cluster_wait() { asm volatile("barrier.cluster.wait;" ::: "memory"); }
__device__ __forceinline__ float ex2(float x) {
  float y;
  asm("ex2.approx.ftz.f32 %0, %1;" : "=f"(y) : "f"(x));
  return y;
}
__device__ __forceinline__ float rcp(float x) {
  float y;
  asm("rcp.approx.ftz.f32 %0, %1;" : "=f"(y) : "f"(x));
  return y;
}
__device__ __forceinline__ uint32_t pack_bf16(float lo, float hi) {
  uint32_t r;
  asm("cvt.rn.bf16x2.f32 %0, %1, %2;" : "=r"(r) : "f"(hi), "f"(lo));
  return r;
}

__device__ __forceinline__ uint32_t pack_f16(float lo, float hi) {
  uint32_t r;
  asm("cvt.rn.f16x2.f32 %0, %1, %2;" : "=r"(r) : "f"(hi), "f"(lo));
  return r;
}

__device__ __forceinline__ uint32_t scale_f16(uint32_t w, float f) {
  float x, y;
  asm("{\n.reg .b16 a, b;\nmov.b32 {a, b}, %2;\ncvt.f32.f16 %0, a;\ncvt.f32.f16 %1, b;\n}" : "=f"(x), "=f"(y) : "r"(w));
  return pack_f16(x * f, y * f);
}

struct Params {
  const int* qk;
  const int* qv;
  const __nv_bfloat16* ks;
  const __nv_bfloat16* kz;
  const __nv_bfloat16* vs;
  const __nv_bfloat16* vz;
  const __nv_bfloat16* q;
  uint8_t* scratch;
  unsigned* flags;
  uint8_t* prob;
};

__device__ __forceinline__ int unit_row(int step, int grp, int mt) {
  return ((step >> 4) * 8 + grp) * kS + (step & 15) * kBN + mt * 8;
}
__device__ __forceinline__ uint8_t* tile_image(const Params& p, int step, int grp, int is_v) {
  return p.scratch + ((size_t)(grp * kRing + (unsigned)step % kRing) * 2 + is_v) * kTileBytes;
}
struct Unit { uint4 x[4]; uint2 s, z; };

__device__ __forceinline__ uint4 ldg128(const void* a) {
  uint4 v;
  asm volatile("ld.global.nc.L1::no_allocate.v4.u32 {%0, %1, %2, %3}, [%4];"
               : "=r"(v.x), "=r"(v.y), "=r"(v.z), "=r"(v.w)
               : "l"(a)
               : "memory");
  return v;
}
__device__ __forceinline__ uint4 ldg128_last_use(const void* a) {
  uint4 v;
  asm volatile("ld.global.nc.L1::no_allocate.L2::cache_hint.v4.u32 {%0, %1, %2, %3}, [%4], %5;"
               : "=r"(v.x), "=r"(v.y), "=r"(v.z), "=r"(v.w)
               : "l"(a), "l"(kEvictFirst)
               : "memory");
  return v;
}
__device__ __forceinline__ uint2 ldg64(const void* a) {
  uint2 v;
  asm volatile("ld.global.nc.v2.u32 {%0, %1}, [%2];" : "=r"(v.x), "=r"(v.y) : "l"(a));
  return v;
}
__device__ __forceinline__ void stg64(uint64_t a, uint32_t x, uint32_t y) {
  asm volatile("st.global.v2.u32 [%0], {%1, %2};" ::"l"(a), "r"(x), "r"(y) : "memory");
}
__device__ __forceinline__ uint32_t bf2_mul(uint32_t a, uint32_t b) {
  uint32_t r;
  asm("mul.rn.bf16x2 %0, %1, %2;" : "=r"(r) : "r"(a), "r"(b));
  return r;
}
__device__ __forceinline__ uint32_t bf2_fma(uint32_t a, uint32_t b, uint32_t c) {
  uint32_t r;
  asm("fma.rn.bf16x2 %0, %1, %2, %3;" : "=r"(r) : "r"(a), "r"(b), "r"(c));
  return r;
}
__device__ __forceinline__ uint32_t h2_fma(uint32_t a, uint32_t b, uint32_t c) {
  uint32_t r;
  asm("fma.rn.f16x2 %0, %1, %2, %3;" : "=r"(r) : "r"(a), "r"(b), "r"(c));
  return r;
}
__device__ __forceinline__ uint32_t h2_mul(uint32_t a, uint32_t b) {
  uint32_t r;
  asm("mul.rn.f16x2 %0, %1, %2;" : "=r"(r) : "r"(a), "r"(b));
  return r;
}
__device__ __forceinline__ float bf_lo(uint32_t w) { return __uint_as_float(w << 16); }
__device__ __forceinline__ float bf_hi(uint32_t w) { return __uint_as_float(w & 0xffff0000u); }
__device__ __forceinline__ uint32_t codes_bf16(uint32_t a, uint32_t b) { return pack_bf16((float)(int)a, (float)(int)b); }
__device__ __forceinline__ uint2 lds64(uint32_t a) {
  uint2 v;
  asm volatile("ld.shared.v2.u32 {%0, %1}, [%2];" : "=r"(v.x), "=r"(v.y) : "r"(a));
  return v;
}
__device__ __forceinline__ uint4 lds128(uint32_t a) {
  uint4 v;
  asm volatile("ld.shared.v4.u32 {%0, %1, %2, %3}, [%4];" : "=r"(v.x), "=r"(v.y), "=r"(v.z), "=r"(v.w) : "r"(a));
  return v;
}
__device__ __forceinline__ uint4 lds128v(uint32_t a) {
  uint4 v;
  asm volatile("ld.shared.v4.u32 {%0, %1, %2, %3}, [%4];" : "=r"(v.x), "=r"(v.y), "=r"(v.z), "=r"(v.w) : "r"(a) : "memory");
  return v;
}
__device__ __forceinline__ void scale_p(uint32_t a, float f0, float f1) {
#pragma unroll 1
  for (int i = 0; i < 16; i++, a += i & 1 ? 8 : 2040) {
    const uint2 x = lds64(a);
    asm volatile("st.shared.v2.u32 [%0], {%1, %2};" ::"r"(a), "r"(scale_f16(x.x, f0)), "r"(scale_f16(x.y, f1)) : "memory");
  }
}
__device__ __forceinline__ uint32_t k_scale(uint32_t s) { return bf2_fma(s, 0x40D540D5u, bf2_mul(s, 0x3BEE3BEEu)); }
__device__ __forceinline__ uint32_t k_zero(uint32_t z) { return bf2_mul(z, 0xBC80BC80u); }
__device__ __forceinline__ uint32_t k_pair(uint32_t x, uint32_t xs, uint32_t z, uint32_t s, uint32_t off) {
  return bf2_fma(bf2_fma(x, xs, z), s, off);
}
constexpr uint32_t kByteScaleK = 0x7F007F00u, kBf16ScaleK = 0x3C803C80u, kByteScaleV = 0x60006000u;
template <bool kIsV>
__device__ __forceinline__ void load_unit(const Params& p, int row0, uint32_t t, Unit& d) {
  const uint32_t hi = t >= 48 ? 1 : 0, q = t - hi * 48;
  const uint8_t* src = (const uint8_t*)((kIsV ? p.qv : p.qk) + (size_t)row0 * kD) + (hi * 3072 + q * 16);
#pragma unroll
  for (int i = 0; i < 4; i++) d.x[i] = ldg128_last_use(src + i * 768);
  if (kIsV) {
    uint32_t o = hi * 8;
    asm("" : "+r"(o));
    d.s = ldg64((const uint8_t*)(p.vs + row0) + o);
    d.z = ldg64((const uint8_t*)(p.vz + row0) + o);
  } else {
    d.s = ldg64((const uint8_t*)(p.ks + (row0 / kGroupTok) * kD) + q * 8);
    d.z = ldg64((const uint8_t*)(p.kz + (row0 / kGroupTok) * kD) + q * 8);
  }
}
__device__ __forceinline__ bool codes_are_bytes(const Unit& d, uint32_t a = 0) {
#pragma unroll
  for (int i = 0; i < 4; i++) a |= d.x[i].x | d.x[i].y | d.x[i].z | d.x[i].w;
  return !__any_sync(0xffffffffu, a > 255);
}
template <int kHalf>
__device__ __forceinline__ uint32_t dup16(uint32_t w) {
  uint32_t v;
  if (kHalf == 0) asm("{\n.reg .b16 a, b;\nmov.b32 {a, b}, %1;\nmov.b32 %0, {a, a};\n}" : "=r"(v) : "r"(w));
  else asm("{\n.reg .b16 a, b;\nmov.b32 {a, b}, %1;\nmov.b32 %0, {b, b};\n}" : "=r"(v) : "r"(w));
  return v;
}
template <bool kIsV>
__device__ __forceinline__ uint64_t unit_dst(const Params& p, int step, int grp, int mt, uint32_t t, int own = kSteps) {
  const uint32_t hi = t >= 48 ? 1 : 0, q = t - hi * 48;
  return (uint64_t)(tile_image(p, step, grp, kIsV && step < own) + mt * (kIsV ? 3072 : 1024)) +
         ((q >> 4) * (kIsV ? 1024 : kChunkBytes) + hi * 512 + (q & 1) * 8 + ((((q & 15) >> 1) ^ (hi * 4)) << 4));
}
__device__ __forceinline__ void store_k(uint64_t dst, int slot, uint32_t t, const Unit& d, uint32_t bars, bool bytes) {
  const uint2 off = lds64(bars + kOffK + slot * (kD * 2) + (t >= 48 ? t - 48 : t) * 8);
  uint32_t x[8];
  if (bytes) {
#pragma unroll
    for (int i = 0; i < 4; i++) {
      x[2 * i] = d.x[i].y * 65536u + d.x[i].x;
      x[2 * i + 1] = d.x[i].w * 65536u + d.x[i].z;
    }
  } else {
#pragma unroll
    for (int i = 0; i < 4; i++) {
      x[2 * i] = codes_bf16(d.x[i].x, d.x[i].y);
      x[2 * i + 1] = codes_bf16(d.x[i].z, d.x[i].w);
    }
  }
  const uint32_t xs = bytes ? kByteScaleK : kBf16ScaleK;
  const uint32_t s0 = k_scale(d.s.x), s1 = k_scale(d.s.y), z0 = k_zero(d.z.x), z1 = k_zero(d.z.y);
#pragma unroll
  for (int i = 0; i < 4; i++)
    stg64((dst ^ (i * 16)) + i * 128, k_pair(x[2 * i], xs, z0, s0, off.x), k_pair(x[2 * i + 1], xs, z1, s1, off.y));
}
constexpr uint32_t kCentreBits = 256 * 0x10001u;
constexpr float kCentre = 256 * (1.f / 16777216);
__device__ __forceinline__ void store_v(uint64_t dst, int step, const Unit& d, uint32_t bars) {
  const uint2 par = lds64(bars + kParV + (step >> 4) * 32);
  const float alpha = __uint_as_float(par.x), centre = __uint_as_float(par.y ^ (step & 8) << 28);
#pragma unroll
  for (int i = 0; i < 4; i++) {
    const uint32_t zw = i < 2 ? d.z.x : d.z.y, sw = i < 2 ? d.s.x : d.s.y;
    const uint32_t zz = (i & 1) ? dup16<1>(zw) : dup16<0>(zw), ss = (i & 1) ? dup16<1>(sw) : dup16<0>(sw);
    auto pair = [&](uint32_t a, uint32_t b) {
      uint32_t v;
      asm("{\n.reg .b32 t;\nsub.rn.bf16x2 t, %1, %2;\nmul.rn.bf16x2 %0, t, %3;\n}"
          : "=r"(v)
          : "r"(codes_bf16(a, b)), "r"(zz), "r"(ss));
      return pack_f16(fmaf(bf_lo(v), alpha, centre), fmaf(bf_hi(v), alpha, centre));
    };
    stg64((dst ^ (i * 16)) + i * 128, pair(d.x[i].x, d.x[i].y), pair(d.x[i].z, d.x[i].w));
  }
}
__device__ __forceinline__ void store_v_any(uint64_t dst, int step, const Unit& d, uint32_t bars) {
  const uint2 par = lds64(bars + kParV + (step >> 4) * 32 + 16);
  const uint32_t z0 = d.z.x - 0x40004000u, z1 = d.z.y - 0x40004000u;
  if (!codes_are_bytes(d, ((z0 | z1) & 0xFC00FC00u) | ((d.s.x | d.s.y) & 0x80008000u)) || par.x == 0) {
    store_v(dst, step, d, bars);
    return;
  }
  const uint2 z = make_uint2(z0 * 8 + 0x84008400u, z1 * 8 + 0x84008400u);
  const uint2 s = make_uint2(h2_mul(d.s.x * 8 + par.y, par.x), h2_mul(d.s.y * 8 + par.y, par.x));
  const uint32_t c2 = kCentreBits ^ (step & 8) * 0x10001000u;
#pragma unroll
  for (int i = 0; i < 4; i++) {
    const uint32_t zw = i < 2 ? z.x : z.y, sw = i < 2 ? s.x : s.y;
    const uint32_t zz = (i & 1) ? dup16<1>(zw) : dup16<0>(zw), ss = (i & 1) ? dup16<1>(sw) : dup16<0>(sw);
    stg64((dst ^ (i * 16)) + i * 128, h2_fma(h2_fma(d.x[i].y * 65536u + d.x[i].x, kByteScaleV, zz), ss, c2),
          h2_fma(h2_fma(d.x[i].w * 65536u + d.x[i].z, kByteScaleV, zz), ss, c2));
  }
}
struct Stat { uint4 s[4], z[4]; };
struct Range { uint4 lo; uint32_t hi; };
__device__ __forceinline__ void stat_load(const Params& p, int head, int j, uint32_t lane, Stat& d) {
  const bool v = lane >= 24;
  const uint32_t off = v ? (head * kS + j * 256) * 2 + (lane - 24) * 16 : (head * 32 + j * 4) * (kD * 2) + lane * 16;
  const uint32_t step = v ? 128 : kD * 2;
  const uint8_t *ps = (const uint8_t*)(v ? p.vs : p.ks), *pz = (const uint8_t*)(v ? p.vz : p.kz);
#pragma unroll
  for (int i = 0; i < 4; i++) {
    uint32_t o = off + i * step;
    asm("" : "+r"(o));
    d.s[i] = ldg128(ps + o);
    d.z[i] = ldg128(pz + o);
  }
}
__device__ __forceinline__ uint32_t range2(uint32_t s, uint32_t z) {
  uint32_t r;
  asm("{\n.reg .b32 m;\nmax.xorsign.abs.bf16x2 m, %2, %3;\nmul.rn.bf16x2 %0, %1, m;\n}"
      : "=r"(r)
      : "r"(s), "r"(z), "r"(0x3F803F80u));
  return r & 0x7fff7fffu;
}
__device__ __forceinline__ void stat_add(const Stat& d, Range& r) {
  auto col = [&](uint32_t& lo, uint32_t a, uint32_t b, uint32_t c, uint32_t e) {
    lo = __vimin3_u16x2(__vimin3_u16x2(lo, a, b), c, e);
    r.hi = __vimax3_u16x2(__vimax3_u16x2(r.hi, a, b), c, e);
  };
  col(r.lo.x, range2(d.s[0].x, d.z[0].x), range2(d.s[1].x, d.z[1].x), range2(d.s[2].x, d.z[2].x), range2(d.s[3].x, d.z[3].x));
  col(r.lo.y, range2(d.s[0].y, d.z[0].y), range2(d.s[1].y, d.z[1].y), range2(d.s[2].y, d.z[2].y), range2(d.s[3].y, d.z[3].y));
  col(r.lo.z, range2(d.s[0].z, d.z[0].z), range2(d.s[1].z, d.z[1].z), range2(d.s[2].z, d.z[2].z), range2(d.s[3].z, d.z[3].z));
  col(r.lo.w, range2(d.s[0].w, d.z[0].w), range2(d.s[1].w, d.z[1].w), range2(d.s[2].w, d.z[2].w), range2(d.s[3].w, d.z[3].w));
}
__device__ __forceinline__ void sts128(uint32_t a, uint32_t x, uint32_t y, uint32_t z, uint32_t w) {
  asm volatile("st.shared.v4.u32 [%0], {%1, %2, %3, %4};" ::"r"(a), "r"(x), "r"(y), "r"(z), "r"(w) : "memory");
}
__device__ __forceinline__ uint4 stat_finish(const Range& r, uint32_t lane) {
  const bool v = lane >= 24;
  const uint32_t lo = __vimin3_u16x2(__vminu2(r.lo.x, r.lo.y), r.lo.z, r.lo.w);
  const float amin = bf_hi(__reduce_min_sync(0xffffffffu, v ? min(lo, lo << 16) : ~0u));
  const float amax = fmaxf(bf_hi(__reduce_max_sync(0xffffffffu, v ? max(r.hi, r.hi << 16) : 0u)), 1e-30f);
  const bool centred = amax <= 2.f * amin && amax <= 1e30f;
  const uint32_t a15 = __float_as_uint((centred ? 0.98f * kCentre * 32768 : 16.f * 32768) * rcp(amax)) & 0xFFFFE000u;
  const float alpha = __uint_as_float(a15) * (1.f / 32768);
  if (lane == 24)
    return make_uint4(__float_as_uint(alpha), centred ? __float_as_uint(kCentre) : 0u, __float_as_uint(rcp(alpha)), 0u);
  if (v) return make_uint4(centred ? (0x3C00u | (a15 >> 13 & 0x3FFu)) * 0x10001u : 0u, ((a15 >> 23) - 239u) * 0x4000400u, 0u, 0u);
  return make_uint4(bf2_mul(r.lo.x, kOffsetFactor), bf2_mul(r.lo.y, kOffsetFactor), bf2_mul(r.lo.z, kOffsetFactor),
                    bf2_mul(r.lo.w, kOffsetFactor));
}
__device__ __forceinline__ void stat_keep(const uint4& x, int wave, uint32_t lane, uint32_t bars) {
  if (lane < 26)
    sts128(bars + lane * 16 + (lane < 24 ? kOffK + (wave & 1) * (kD * 2) : kParV - 24 * 16 + wave * 32), x.x, x.y, x.z, x.w);
}
__device__ __forceinline__ void prefetch_bulk(const void* g, uint32_t bytes) {
  asm volatile("cp.async.bulk.prefetch.L2.global [%0], %1;" ::"l"(g), "r"(bytes) : "memory");
}
__device__ __forceinline__ void publish(const Params& p, int flag, int grp, int warps) {
  asm volatile(
      "{\n.reg .pred p;\nelect.sync _|p, 0xffffffff;\n@p red.release.gpu.global.add.u32 [%0], %1;\n}" ::"l"(
          p.flags + grp * kFlagsPerGroup + flag),
      "r"(warps)
      : "memory");
}
__device__ __forceinline__ void flag_wait(const unsigned* f) {
#pragma unroll 1
  for (int n = 0; n < kFlagPolls; n++) {
    unsigned v;
    asm volatile("ld.acquire.gpu.global.u32 %0, [%1];" : "=r"(v) : "l"(f) : "memory");
    if (__all_sync(0xffffffffu, v >= kFlagTarget)) break;
  }
  asm volatile("fence.proxy.async.global;" ::: "memory");
}

__device__ __forceinline__ void helper_cta(const Params& p, const CUtensorMap& tmq, uint32_t sbase, uint32_t t_start) {
  constexpr int kFullQ = 0, kEmptyQ = 32, kDone = 64, kFullK = 72;
  const uint32_t bars = sbase + kSmemBar, sq = sbase + kMaxTail * kTileBytes;
  const int warp = __shfl_sync(0xffffffffu, threadIdx.x >> 5, 0);
  const int lane = threadIdx.x & 31;
  const int grp0 = blockIdx.x - kOwners;
  auto job_grp = [&](int n) { return (int)(kJobs >> (16 * n + 4 * grp0) & 7); };
  auto job_row = [&](int n) { return ((kWaves - 1) * 8 + job_grp(n)) * kS; };
  auto job_images = [&](int n) { return p.prob + (size_t)(kHelperImages + job_grp(n) * (kMaxTail * kTileBytes)); };
  if (threadIdx.x == 0) {
    for (int i = 0; i < 3; i++) {
      mbar_init(bars + kFullQ + 8 * i, 1);
      mbar_init(bars + kEmptyQ + 8 * i, 4);
    }
    mbar_init(bars + kDone, 8);
    mbar_init(bars + kFullK, 1);
    asm volatile("fence.proxy.async.shared::cta;" ::: "memory");
  }
  auto sleep_until = [&](uint32_t t) {
    while (now_clk() - t_start < t) __nanosleep(200);
  };
  auto wait_long = [&](uint32_t bar, uint32_t parity) {
#pragma unroll 1
    for (int k = 0; k < kFlagPolls && !mbar_try(bar, parity); k++) __nanosleep(200);
  };
  sleep_until(kHelperPrepare);
  if (warp < 6) {
    const int head = job_row(warp & 1) / kS - (warp >> 1) * 8, blocks = tail_blocks(head & 7);
    if (warp < 2 && elect_one()) prefetch_bulk(p.qk + (size_t)(head * kS + kS - blocks * kBN) * kD, blocks * 2 * kTileBytes);
    __syncwarp();
    Range r = {make_uint4(~0u, ~0u, ~0u, ~0u), 0u};
#pragma unroll 1
    for (int j = 0; j < 8; j += 2) {
      Stat a, b;
      stat_load(p, head, j, lane, a);
      stat_load(p, head, j + 1, lane, b);
      stat_add(a, r);
      stat_add(b, r);
    }
    const uint4 x = stat_finish(r, lane);
    if (warp < 2) stat_keep(x, warp, lane, bars);
    *(uint4*)(p.prob + kHeadStats + head * 512 + lane * 16) = x;
  }
  __syncthreads();
  if (threadIdx.x < 2)
    asm volatile("red.release.gpu.global.add.u32 [%0], %1;" ::"l"(p.flags + kFlagStats + job_grp(threadIdx.x)), "n"(kFlagTarget)
                 : "memory");
#pragma unroll 1
  for (int n = 0; n < 2; n++) {
    const int team = warp / 3, units = 16 * tail_blocks(job_grp(n));
    const uint32_t t = threadIdx.x - team * 96, hi = t >= 48 ? 1 : 0, q = t - hi * 48;
    const int row = job_row(n) + kS - units * 8;
    const uint64_t dst = (uint64_t)job_images(n) +
                         ((q >> 4) * kChunkBytes + hi * 512 + (q & 1) * 8 + ((((q & 15) >> 1) ^ (hi * 4)) << 4));
    auto unit_at = [&](int m) { return (m >> 4) * kTileBytes + (m & 15) * 1024; };
#pragma unroll 1
    for (int m = 4 * team; m < units; m += 16) {
      Unit u[4];
#pragma unroll
      for (int i = 0; i < 4; i++) load_unit<false>(p, row + (m + i) * 8, t, u[i]);
#pragma unroll
      for (int i = 0; i < 4; i++) store_k(dst + unit_at(m + i), n, t, u[i], bars, codes_are_bytes(u[i]));
    }
  }
  __threadfence();
  __syncthreads();
  if (warp >= 8) {
    asm volatile("setmaxnreg.dec.sync.aligned.u32 104;");
    if (warp == 8) {
      sleep_until(kHelperDelay);
      uint32_t slot = 0, parity = 1;
#pragma unroll 1
      for (int z = 0; z < 64; z++) {
        const int n = z >> 5, blocks = tail_blocks(job_grp(n));
        if (z == 0 || z == 35) {
          if (n) mbar_spin(bars + kDone, 0);
          asm volatile("fence.proxy.async.global;" ::: "memory");
          if (elect_one()) {
            mbar_expect_tx(bars + kFullK, blocks * kTileBytes);
            bulk_load(sbase, job_images(n), blocks * kTileBytes, bars + kFullK);
          }
          __syncwarp();
        }
        const int half = blocks == 1 ? (z & 28) + (z & 1) * 2 + ((z >> 1) & 1) : z & 31;
        const uint32_t bar = bars + kFullQ + 8 * slot;
        mbar_spin(bars + kEmptyQ + 8 * slot, parity);
        if (elect_one()) {
          mbar_expect_tx(bar, kTileBytes / 2);
#pragma unroll
          for (int c = 0; c < 3; c++)
            tma_load_2d(sq + slot * (kTileBytes / 2) + c * 8192, &tmq, c * 64, job_row(n) + half * 64, bar);
          const int v = min(z + 2 * 3, 63);
          prefetch_bulk(p.q + (size_t)(job_row(v >> 5) + (v & 31) * 64) * kD, kTileBytes / 2);
          if (z == 24) prefetch_bulk(job_images(1), tail_blocks(job_grp(1)) * kTileBytes);
        }
        __syncwarp();
        if (++slot == 3) {
          slot = 0;
          parity ^= 1;
        }
      }
    } else if (warp == 9) {
#pragma unroll 1
      for (int n = 0; n < 2; n++) {
        wait_long(bars + kDone, n);
        if (elect_one()) {
          asm volatile("red.release.gpu.global.add.u32 [%0], %1;" ::"l"(p.flags + kFlagHelper + job_grp(n)), "n"(kFlagTarget)
                       : "memory");
        }
        __syncwarp();
      }
    }
    return;
  }
  asm volatile("setmaxnreg.inc.sync.aligned.u32 200;");
  const int wg = warp >> 2;
  float A[64], B[64];
#pragma unroll
  for (int i = 0; i < 64; i++) asm volatile("" : "=f"(A[i]), "=f"(B[i]));
  int n, blocks;
  auto issue = [&](float (&S)[64], int tile, int j) {
    const uint32_t z = 32 * n + (blocks == 1 ? (tile >> 1) * 4 + 2 * wg + (tile & 1) : 2 * tile + wg);
    const uint32_t turn = z * 43 >> 7, slot = z - 3 * turn;
    if (j == 0) mbar_wait(bars + kFullQ + 8 * slot, turn & 1);
    const uint32_t kb = desc_lo(sbase, 16) + j * (kTileBytes >> 4);
    const uint32_t qb = desc_lo(sq, 16) + slot * (kTileBytes >> 5);
    bar_sync(2 + wg);
    wg_fence();
    wgmma_new_n128(S, desc64<1024>(qb), desc64<1024>(kb));
#pragma unroll
    for (int kk = 1; kk < 12; kk++)
      wgmma_ss_n128(S, desc64<1024>(qb + (kk >> 2) * 512 + (kk & 3) * 2), desc64<1024>(kb + (kk >> 2) * 1024 + (kk & 3) * 2), 1);
    wg_commit();
    bar_arrive(3 - wg);
    return bars + kEmptyQ + 8 * slot;
  };
  float r0, r1;
  auto finish = [&](float (&S)[64], int tile, int j) {
    pin(S);
    int a0 = 0, a1 = 0;
    uint32_t u0 = ~0u, u1 = ~0u;
#pragma unroll
    for (int i = 0; i < 64; i += 4) {
      a0 = __vimax3_s32(a0, __float_as_int(S[i]), __float_as_int(S[i + 1]));
      a1 = __vimax3_s32(a1, __float_as_int(S[i + 2]), __float_as_int(S[i + 3]));
      if (i < 16) {
        u0 = __vimin3_u32(u0, __float_as_uint(S[i]), __float_as_uint(S[i + 1]));
        u1 = __vimin3_u32(u1, __float_as_uint(S[i + 2]), __float_as_uint(S[i + 3]));
      }
    }
    uint8_t* out = p.prob + (size_t)((job_grp(n) * 16 + tile) * kProbBytes);
    float d0 = 0.f, d1 = 0.f;
    if (j == 0) r0 = r1 = 0.f;
    if (__any_sync(0xffffffffu, max(a0, a1) > __float_as_int(kLazyAbove) || max(u0, u1) >= __float_as_uint(-kLazyBelow))) {
      r0 = -INFINITY;
      d0 = S[0];
      d1 = S[2];
#pragma unroll
      for (int i = 0; i < 64; i += 4) {
        d0 = fmaxf(d0, fmaxf(S[i], S[i + 1]));
        d1 = fmaxf(d1, fmaxf(S[i + 2], S[i + 3]));
      }
      d0 = fmaxf(d0, __shfl_xor_sync(0xffffffffu, d0, 1));
      d1 = fmaxf(d1, __shfl_xor_sync(0xffffffffu, d1, 1));
      d0 = fmaxf(d0, __shfl_xor_sync(0xffffffffu, d0, 2));
      d1 = fmaxf(d1, __shfl_xor_sync(0xffffffffu, d1, 2));
#pragma unroll
      for (int i = 0; i < 64; i++) S[i] -= (i & 2) ? d1 : d0;
    }
    float l0 = 0.f, l1 = 0.f;
#pragma unroll
    for (int i = 0; i < 64; i += 4) {
#pragma unroll
      for (int k = 0; k < 4; k++) S[i + k] = ex2(S[i + k]);
      l0 += S[i] + S[i + 1];
      l1 += S[i + 2] + S[i + 3];
    }
    pin(S);
    l0 += __shfl_xor_sync(0xffffffffu, l0, 1);
    l1 += __shfl_xor_sync(0xffffffffu, l1, 1);
    l0 += __shfl_xor_sync(0xffffffffu, l0, 2);
    l1 += __shfl_xor_sync(0xffffffffu, l1, 2);
    uint8_t* dst = out + kProbData + (2 * j + wg) * 16384 + (threadIdx.x & 127) * 16;
#pragma unroll
    for (int i = 0; i < 8; i++)
      asm volatile("st.global.L1::no_allocate.v4.u32 [%0], {%1, %2, %3, %4};" ::"l"(dst + i * 2048),
                   "r"(pack_f16(S[8 * i], S[8 * i + 1])), "r"(pack_f16(S[8 * i + 2], S[8 * i + 3])),
                   "r"(pack_f16(S[8 * i + 4], S[8 * i + 5])), "r"(pack_f16(S[8 * i + 6], S[8 * i + 7]))
                   : "memory");
    l0 *= 0.25f;
    l1 *= 0.25f;
    r0 += l0;
    r1 += l1;
    if ((lane & 3) == 0) {
      *(float4*)(out + kProbExtra + j * 1024 + threadIdx.x * 4) = make_float4(d0, d1, l0, l1);
      if (j == blocks - 1) stg64((uint64_t)(out + threadIdx.x * 2), __float_as_uint(r0), __float_as_uint(r1));
    }
  };
  if (wg == 1) bar_arrive(2);
#pragma unroll 1
  for (n = 0; n < 2; n++) {
    blocks = tail_blocks(job_grp(n));
    wait_long(bars + kFullK, n);
    int tile = 0, j = 0, tile_b = -1, j_b = 0;
#pragma unroll 1
    for (;;) {
      const uint32_t qa = issue(A, tile, tile < 16 ? j : 1);
      wg_wait<1>();
      if (tile_b >= 0) finish(B, tile_b, j_b);
      wg_wait<0>();
      if (tile == 16) break;
      const bool wrap = j == blocks - 1;
      if (wrap && lane == 0) mbar_arrive_local(qa);
      tile_b = tile + wrap;
      j_b = wrap ? 0 : j + 1;
      const uint32_t qb = issue(B, tile_b, j_b);
      wg_wait<1>();
      finish(A, tile, j);
      asm volatile("st.volatile.shared.f32 [%0], %1;" ::"r"(bars + kDummy), "f"(r1) : "memory");
      wg_wait<0>();
      const bool wrap_b = j_b == blocks - 1;
      if (wrap_b && lane == 0) mbar_arrive_local(qb);
      tile = tile_b + wrap_b;
      j = wrap_b ? 0 : j_b + 1;
    }
    __syncwarp();
    if (lane == 0) mbar_arrive_local(bars + kDone);
  }
}

__global__ void __cluster_dims__(2, 1, 1) __launch_bounds__(384, 1)
    attn_kernel(const Params p, const __grid_constant__ CUtensorMap tmq, const __grid_constant__ CUtensorMap tmo) {
  extern __shared__ uint8_t smem_raw[];
  const uint32_t t_start = now_clk();
  const uint32_t sbase = ((uint32_t)__cvta_generic_to_shared(smem_raw) + 1023) & ~1023u;
  if (blockIdx.x >= kOwners) {
    helper_cta(p, tmq, sbase, t_start);
    return;
  }
  const uint32_t bars = sbase + kSmemBar;
  const int grp = blockIdx.x >> 4, mt = blockIdx.x & 15;
  const int tail = __shfl_sync(0xffffffffu, tail_blocks(grp), 0), own = kSteps - tail;
  const uint32_t tail_stage = tail == 3 ? kSmemQ : kSmemV + kTileBytes;
  const int warp = __shfl_sync(0xffffffffu, threadIdx.x >> 5, 0);
  const int lane = threadIdx.x & 31;

  auto load_q = [&](int tile, int w) {
    const uint32_t bar = bars + kBarFullQ + 8 * w;
    const int row = (tile * 8 + grp) * kS + mt * 128 + w * 64;
    mbar_expect_tx(bar, 16384);
    mbar_expect_tx(bars + kBarFullQ2 + 8 * w, 8192);
#pragma unroll
    for (int c = 0; c < 3; c++)
      tma_load_2d(sbase + kSmemQ + w * 24576 + c * 8192, &tmq, c * 64, row, c < 2 ? bar : bars + kBarFullQ2 + 8 * w);
  };
  if (warp == 8 && elect_one()) {
    mbar_init(bars + kBarParams, 1);
    mbar_init(bars + kBarCodes, 1);
    mbar_init(bars + kBarUnits, 1);
    asm volatile("fence.proxy.async.shared::cta;" ::: "memory");
    mbar_expect_tx(bars + kBarParams, 32768);
    bulk_load(sbase + kSmemV, p.ks + grp * 32 * kD, 12288, bars + kBarParams);
    bulk_load(sbase + kSmemV + 12288, p.kz + grp * 32 * kD, 12288, bars + kBarParams);
    bulk_load(sbase + kSmemV + 24576, p.vs + grp * kS, 4096, bars + kBarParams);
    bulk_load(sbase + kSmemV + 36864, p.vz + grp * kS, 4096, bars + kBarParams);
  }
  __syncwarp();
  if (warp == 8) {
    asm volatile("bar.arrive 6, 160;" ::: "memory");
    while (now_clk() - t_start < ((uint32_t)(kCodeDelays >> 8 * grp) & 255) * 32) {}
  }
  const int row_k0 = grp * kS + (blockIdx.x & 1) * 64;
  if (warp == 8 && elect_one()) {
    mbar_expect_tx(bars + kBarUnits, 4 * 6144);
#pragma unroll
    for (int j = 0; j < 4; j++)
      bulk_load(sbase + kSmemK + 3 * kChunkBytes + j * 6144,
                (j & 1 ? p.qv : p.qk) + (size_t)unit_row((j >> 1) + 1 - (j & 1), grp, mt) * kD, 6144, bars + kBarUnits);
    mbar_expect_tx(bars + kBarCodes, kTileBytes);
    bulk_load(sbase + kSmemV + kTileBytes, p.qk + (size_t)row_k0 * kD, kTileBytes, bars + kBarCodes);
    for (int i = 0; i < 2; i++) {
      mbar_init(bars + kBarFullK01 + 8 * i, 1);
      mbar_init(bars + kBarFullV + 8 * i, 1);
      mbar_init(bars + kBarEmptyK12 + 8 * i, 16);
      mbar_init(bars + kBarEmptyV + 8 * i, 16);
      mbar_init(bars + kBarFullQ + 8 * i, 1);
      mbar_init(bars + kBarFullQ2 + 8 * i, 1);
      mbar_init(bars + kBarEmptyQ + 8 * i, 4);
      mbar_init(bars + kBarStage + 8 * i, 4);
      mbar_init(bars + kBarStaged + 8 * i, 4);
      for (int c = 0; c < 3; c++) mbar_init(bars + kBarTail + 24 * i + 8 * c, 4);
    }
    mbar_init(bars + kBarFullK2, 1);
    mbar_init(bars + kBarFullV2, 1);
    mbar_init(bars + kBarEmptyK0, 16);
    asm volatile("st.shared.u32 [%0], %1;" ::"r"(bars + kProgress), "r"(0) : "memory");
    asm volatile("fence.mbarrier_init.release.cluster;" ::: "memory");
    asm volatile("fence.acq_rel.cta;" ::: "memory");
    asm volatile("prefetch.tensormap [%0];" ::"l"(&tmq) : "memory");
  }
  __syncwarp();
  cluster_arrive();
  const bool helper = warp > 8 || (warp >= 4 && warp < 7);
  const uint32_t th = warp < 8 ? threadIdx.x & 127 : threadIdx.x - 288;
  const int it = warp < 8 ? 1 : 0;
  if (warp == 8) {
    while (now_clk() - t_start < ((uint32_t)(kQueryDelays >> 8 * grp) & 255) * 32) {}
#pragma unroll 1
    for (int w = 0; w < 2; w++)
      if (elect_one()) load_q(0, w);
  }
  __syncwarp();
  if (warp < 4) {
    asm volatile("bar.sync 6, 160;" ::: "memory");
    Range r = {make_uint4(~0u, ~0u, ~0u, ~0u), 0u};
    mbar_spin(bars + kBarParams, 0);
    const uint32_t pitch = lane >= 24 ? 128 : kD * 2;
    uint32_t src = sbase + kSmemV + (lane >= 24 ? 24576 - 384 : 0) + lane * 16 + warp * 8 * pitch;
#pragma unroll 1
    for (int j = 0; j < 2; j++) {
      Stat st;
#pragma unroll
      for (int i = 0; i < 4; i++, src += pitch) {
        st.s[i] = lds128(src);
        st.z[i] = lds128(src + 12288);
      }
      stat_add(st, r);
    }
    const uint32_t part = sbase + kSmemV + 40960 + lane * 16;
    sts128(part + warp * 1024, r.lo.x, r.lo.y, r.lo.z, r.lo.w);
    sts128(part + warp * 1024 + 512, r.hi, 0u, 0u, 0u);
    asm volatile("bar.sync 4, 128;" ::: "memory");
#pragma unroll
    for (int j = 1; j < 4; j++) {
      const uint32_t other = part + ((warp + j) & 3) * 1024;
      const uint4 lo = lds128(other);
      r.lo = make_uint4(__vminu2(r.lo.x, lo.x), __vminu2(r.lo.y, lo.y), __vminu2(r.lo.z, lo.z), __vminu2(r.lo.w, lo.w));
      r.hi = __vmaxu2(r.hi, lds64(other + 512).x);
    }
    stat_keep(stat_finish(r, lane), 0, lane, bars);
    __syncwarp();
    if (warp == 0) asm volatile("bar.arrive 5, 224;" ::: "memory");
  }
  if (helper) {
    asm volatile("bar.sync 5, 224;" ::: "memory");
    const uint32_t hi = th >= 48 ? 1 : 0, q = th - hi * 48;
    const uint32_t src = sbase + kSmemK + 3 * kChunkBytes + it * 12288 + hi * 3072 + q * 16;
    const uint32_t kp = sbase + kSmemV + (2 * it + 2 + (mt >> 3)) * (kD * 2) + q * 8;
    const uint32_t vp = sbase + kSmemV + 24576 + (it * kBN + mt * 8 + hi * 4) * 2;
    Unit k0, v0;
    k0.s = lds64(kp);
    k0.z = lds64(kp + 12288);
    v0.s = lds64(vp);
    v0.z = lds64(vp + 12288);
    mbar_spin(bars + kBarUnits, 0);
#pragma unroll
    for (int i = 0; i < 4; i++) {
      k0.x[i] = lds128(src + i * 768);
      v0.x[i] = lds128(src + 6144 + i * 768);
    }
    store_k(unit_dst<false>(p, it + 1, grp, mt, th), 0, th, k0, bars, false);
    store_v(unit_dst<true>(p, it, grp, mt, th), it, v0, bars);
    if (warp < 8) asm volatile("bar.arrive 3, 192;" ::: "memory");
  }
  cluster_wait();
  if (warp < 4) {
    uint2 o0[3], s0[3], z0[3];
#pragma unroll
    for (int c = 0; c < 3; c++) {
      const uint32_t col = c * 128 + (threadIdx.x & 15) * 8;
      o0[c] = lds64(bars + kOffK + col);
      s0[c] = lds64(sbase + kSmemV + (blockIdx.x & 1) * (kD * 2) + col);
      z0[c] = lds64(sbase + kSmemV + 12288 + (blockIdx.x & 1) * (kD * 2) + col);
      s0[c] = make_uint2(k_scale(s0[c].x), k_scale(s0[c].y));
      z0[c] = make_uint2(k_zero(z0[c].x), k_zero(z0[c].y));
    }
    mbar_spin(bars + kBarCodes, 0);
    const uint32_t r = threadIdx.x >> 4, half = sbase + kSmemK + (blockIdx.x & 1) * (kChunkBytes / 2);
    uint32_t src = sbase + kSmemV + kTileBytes + r * 768 + (threadIdx.x & 15) * 16;
    uint32_t dst = half + r * 128 + (threadIdx.x & 1) * 8 + ((((threadIdx.x & 15) >> 1) ^ r) << 4);
#pragma unroll 1
    for (int i = 0; i < 4; i++, src += 16 * 768, dst += 2048) {
      uint4 x[6];
#pragma unroll
      for (int j = 0; j < 6; j++)
        asm volatile("ld.shared.v4.u32 {%0, %1, %2, %3}, [%4];"
                     : "=r"(x[j].x), "=r"(x[j].y), "=r"(x[j].z), "=r"(x[j].w)
                     : "r"(src + (j & 1) * 8 * 768 + (j >> 1) * 256));
#pragma unroll
      for (int j = 0; j < 6; j++)
        asm volatile("st.shared.v2.u32 [%0], {%1, %2};" ::"r"(dst + (j & 1) * 1024 + (j >> 1) * kChunkBytes),
                     "r"(k_pair(codes_bf16(x[j].x, x[j].y), kBf16ScaleK, z0[j >> 1].x, s0[j >> 1].x, o0[j >> 1].x)),
                     "r"(k_pair(codes_bf16(x[j].z, x[j].w), kBf16ScaleK, z0[j >> 1].y, s0[j >> 1].y, o0[j >> 1].y)));
    }
    asm volatile("fence.proxy.async.shared::cta;" ::: "memory");
    asm volatile("bar.sync 4, 128;" ::: "memory");
    if (threadIdx.x == 0) {
      mbar_expect_tx(bars + kBarFullK01, kChunkBytes);
      mbar_expect_tx(bars + kBarFullK2, kChunkBytes / 2);
#pragma unroll
      for (int c = 0; c < 3; c++)
        bulk_copy_peer(half + c * kChunkBytes, kChunkBytes / 2, bars + (c < 2 ? kBarFullK01 : kBarFullK2),
                       (blockIdx.x & 1) ^ 1);
    }
  }

  if (warp >= 8) {
    asm volatile("setmaxnreg.dec.sync.aligned.u32 56;");
    if (warp == 8) {
      const uint32_t rank = blockIdx.x & 1;
      const unsigned* flags = p.flags + grp * kFlagsPerGroup;
      const uint8_t* const images = tile_image(p, 0, grp, 0);
      auto image = [&](int step, uint32_t offset) { return images + ((step & (kRing - 1)) * (2 * kTileBytes) + offset); };
      uint32_t k_dst = sbase + kSmemK + 2 * kChunkBytes + rank * (kChunkBytes / 2);
      auto next_slot = [&]() {
        k_dst += kChunkBytes;
        if (k_dst >= sbase + kSmemV) k_dst -= 5 * kChunkBytes;
        return k_dst;
      };
      auto k_chunk = [&](uint32_t dst, int step, int c, uint32_t bar) {
        bulk_load_mc(dst, image(step, c * kChunkBytes + rank * (kChunkBytes / 2)), kChunkBytes / 2, bar);
      };
      auto load_k01 = [&](int step) {
        const uint32_t bar = bars + kBarFullK01 + 8 * (step & 1);
        const uint32_t d0 = next_slot(), d1 = next_slot();
        if (elect_one()) {
          mbar_expect_tx(bar, 2 * kChunkBytes);
          k_chunk(d0, step, 0, bar);
          k_chunk(d1, step, 1, bar);
        }
        __syncwarp();
      };
      auto load_k2 = [&](int step) {
        const uint32_t d = next_slot();
        if (elect_one()) {
          mbar_expect_tx(bars + kBarFullK2, kChunkBytes);
          k_chunk(d, step, 2, bars + kBarFullK2);
        }
        __syncwarp();
      };
      auto v_part = [&](int step, uint32_t len, uint32_t bar) {
        bulk_load_mc(sbase + kSmemV + (step & 1) * kTileBytes + rank * (len / 2),
                     image(step, kTileBytes + rank * (len / 2)), len / 2, bar);
      };
      auto load_vt = [&](int step) {
        const uint32_t bar = bars + kBarFullV + 8 * (step & 1);
        if (elect_one()) {
          mbar_expect_tx(bar, kTileBytes);
          v_part(step, kTileBytes, bar);
        }
        __syncwarp();
      };
      auto wait_flag = [&](int f) {
        flag_wait(flags + f);
      };
      auto store_out = [&](int tile, int w) {
        mbar_spin(bars + kBarStaged + 8 * w, tile & 1);
        asm volatile("fence.proxy.async.shared::cta;" ::: "memory");
        if (elect_one()) {
          const int row = (tile * 8 + grp) * kS + mt * 128 + w * 64;
#pragma unroll
          for (int c = 0; c < 3; c++)
            tma_store_2d(&tmo, sbase + kSmemV + w * kTileBytes + kTileBytes / 2 + c * 8192, c * 64, row);
          asm volatile("cp.async.bulk.commit_group;" ::: "memory");
        }
        __syncwarp();
      };
      auto reload_v = [&](int w, int step, uint32_t bar) {
        asm volatile("cp.async.bulk.wait_group.read 0;" ::: "memory");
        if (elect_one())
          bulk_load(sbase + kSmemV + w * kTileBytes + kTileBytes / 2, image(step, kTileBytes + kTileBytes / 2), kTileBytes / 2, bar);
        __syncwarp();
      };
      const uint8_t* prob = p.prob + (size_t)(blockIdx.x * kProbBytes);
      const int poll_step = (own - 3) | 1;
      auto load_p = [&](uint32_t dst, int q, uint32_t bar) {
        bulk_load(dst - rank * (kChunkBytes / 2), prob + kProbData + q * kChunkBytes, kChunkBytes, bar);
      };
      wait_flag(1);
      load_k01(1);
#pragma unroll 1
      for (int s = 0;; s++) {
        const bool newq = (s & 15) == 15;
        if (newq) {
          mbar_spin(bars + kBarEmptyQ, (s >> 4) & 1);
          if (elect_one()) load_q((s >> 4) + 1, 0);
          __syncwarp();
        }
        mbar_spin(bars + kBarEmptyK0, s & 1);
        load_k2(s + 1);
        if (s == 0) {
          if (elect_one()) {
            mbar_expect_tx(bars + kBarFullV, kTileBytes / 2);
            mbar_expect_tx(bars + kBarFullV2, kTileBytes / 2);
            v_part(0, kTileBytes / 2, bars + kBarFullV);
            bulk_load_mc(sbase + kSmemV + kTileBytes / 2 + rank * (kTileBytes / 4),
                         image(0, kTileBytes + kTileBytes / 2 + rank * (kTileBytes / 4)), kTileBytes / 4,
                         bars + kBarFullV2);
          }
          __syncwarp();
        }
        const bool tile_end = (s & 15) == 0 && s > 0;
        if (tile_end) {
          store_out((s >> 4) - 1, 0);
          reload_v(0, s, bars + kBarFullV2);
        }
        if (newq) {
          mbar_spin(bars + kBarEmptyQ + 8, (s >> 4) & 1);
          if (elect_one()) load_q((s >> 4) + 1, 1);
          __syncwarp();
        }
        if (s & 1) {
          uint32_t f = grp * kFlagsPerGroup + s + 2;
          if (lane == 31 && s == kStatStep) f = kFlagStats + grp;
          if (lane == 31 && s == poll_step) f = kFlagHelper + grp;
          f *= 4;
          asm("" : "+r"(f));
          flag_wait((const unsigned*)((const uint8_t*)p.flags + f));
        }
        if (s == poll_step && elect_one()) prefetch_bulk(prob, kProbData + tail * 2 * kChunkBytes);
        __syncwarp();
        mbar_spin(bars + kBarEmptyK12 + 8 * (s & 1), (s >> 1) & 1);
        if (s + 2 < own) {
          load_k01(s + 2);
        } else {
          const uint32_t d0 = next_slot(), d1 = next_slot();
          if (elect_one()) {
            mbar_expect_tx(bars + kBarUnits, 2 * kChunkBytes + 512);
            bulk_load(bars + kOffK, prob, 512, bars + kBarUnits);
            load_p(d0, 0, bars + kBarUnits);
            load_p(d1, 1, bars + kBarUnits);
          }
          __syncwarp();
        }
        mbar_spin(bars + kBarEmptyV + 8 * ((s + 1) & 1), (((s + 1) >> 1) & 1) ^ 1);
        if (newq || tile_end) {
          const uint32_t bar = bars + kBarFullV + 8 * ((s + 1) & 1);
          if (elect_one()) {
            mbar_expect_tx(bar, newq ? kTileBytes / 2 : kTileBytes);
            if (newq) mbar_expect_tx(bars + kBarFullV2, kTileBytes / 2);
            v_part(s + 1, kTileBytes / 2, bar);
          }
          __syncwarp();
          if (tile_end) {
            store_out((s >> 4) - 1, 1);
            reload_v(1, s + 1, bar);
          }
        } else {
          load_vt(s + 1);
        }
        if ((s & 15) == kStatStep && s < kSteps - 16) {
          uint4 x;
          asm volatile("ld.global.L1::no_allocate.v4.u32 {%0, %1, %2, %3}, [%4];"
                       : "=r"(x.x), "=r"(x.y), "=r"(x.z), "=r"(x.w)
                       : "l"(p.prob + (kHeadStats + (((s >> 4) + 1) * 8 + grp) * 512 + lane * 16))
                       : "memory");
          stat_keep(x, (s >> 4) + 1, lane, bars);
          __syncwarp();
        }
        asm volatile("st.volatile.shared.u32 [%0], %1;" ::"r"(bars + kProgress), "r"(s + 1) : "memory");
        if (s < kSteps - 16) {
          if ((s & 12) == 8) {
            const uint8_t* qn = (const uint8_t*)(p.q + (size_t)((((s >> 4) + 1) * 8 + grp) * kS + mt * 128) * kD);
            if (elect_one()) prefetch_bulk(qn + (s & 3) * 12288, 12288);
            __syncwarp();
          }
        }
        if (s == own - 2) break;
      }
      wait_flag(kSteps - 1);
      uint32_t vw = pick(tail, kPlacesV<1>, kPlacesV<2>, kPlacesV<3>);
      int q = 2;
#pragma unroll 1
      for (int i = 0;; i++) {
        vw >>= 8;
        const uint32_t bar = bars + (vw >> 1 & 0x78);
        mbar_spin(i == 0 ? bars + kBarEmptyK12 + 8 * ((own - 1) & 1) : bar + (kBarEmptyV - kBarFullV),
                  (i == 0 ? own - 1 : (vw ^ 4) >> 1) >> 1 & 1);
        if (i == 1) mbar_spin(bars + kBarFullQ, 0);
        if (elect_one()) {
          mbar_expect_tx(bar, kTileBytes);
          bulk_load_mc(sbase + (vw & 11) * 16384 + rank * (kTileBytes / 2), image(own + i, rank * (kTileBytes / 2)),
                       kTileBytes / 2, bar);
        }
        __syncwarp();
#pragma unroll 1
        for (; q < min(2 * i + 3, 2 * tail); q++) {
          const uint32_t d = next_slot();
          const uint32_t pb = bars + ((kBarCodes | kBarParams << 8 | (kBarFullQ + 8) << 16 | kBarFullQ2 << 24) >> (8 * q - 16) & 255);
          if (elect_one()) {
            mbar_expect_tx(pb, kChunkBytes);
            load_p(d, q, pb);
          }
          __syncwarp();
        }
        if (i == tail - 1) break;
      }
      unsigned done = 0;
      if (lane == 0)
        asm volatile("atom.global.inc.u32 %0, [%1], %2;" : "=r"(done) : "l"(p.flags + kFlagDone), "n"(kOwners - 1) : "memory");
      if (__shfl_sync(0xffffffffu, done, 0) == kOwners - 1) {
#pragma unroll
        for (int j = 0; j < 8 * kFlagsPerGroup / 128; j++) ((uint4*)p.flags)[j * 32 + lane] = make_uint4(0, 0, 0, 0);
        if (lane < 4) ((uint4*)p.flags)[kFlagHelper / 4 + lane] = make_uint4(0, 0, 0, 0);
      }
      __syncwarp();
      cluster_arrive();
#pragma unroll 1
      for (int j = 0; j < 6; j++) {
        const int w = (j + 1) >> 2;
        mbar_spin(bars + kBarTail + 8 * j, 0);
        asm volatile("fence.proxy.async.shared::cta;" ::: "memory");
        if (elect_one())
          tma_store_2d(&tmo, sbase + tail_stage + j * 8192, (j - 3 * w) * 64,
                       ((kWaves - 1) * 8 + grp) * kS + mt * 128 + w * 64);
        __syncwarp();
      }
      if (elect_one()) asm volatile("cp.async.bulk.commit_group;\ncp.async.bulk.wait_group.read 0;" ::: "memory");

    } else {
      const uint32_t t = threadIdx.x - 288;
      auto throttle = [&](int i) {
#pragma unroll 1
        for (int n = 0; n < 100000; n++) {
          int prog;
          asm volatile("ld.volatile.shared.u32 %0, [%1];" : "=r"(prog) : "r"(bars + kProgress) : "memory");
          if (__all_sync(0xffffffffu, i <= prog + kLead)) break;
          __nanosleep(200);
        }
      };
      asm volatile("bar.sync 3, 192;" ::: "memory");
      publish(p, 1, grp, 1);
      Unit v, k;
      load_unit<false>(p, unit_row(3, grp, mt), t, k);
      load_unit<true>(p, unit_row(2, grp, mt), t, v);
#pragma unroll 1
      for (int i = 2; i < kSteps; i++) {
        throttle(i - (i >= own));
        if (i + 1 < own) store_k(unit_dst<false>(p, i + 1, grp, mt, t), ((i + 1) >> 4) & 1, t, k, bars, codes_are_bytes(k));
        load_unit<false>(p, unit_row(min(i + 2, own - 1), grp, mt), t, k);
        store_v_any(unit_dst<true>(p, i, grp, mt, t, own), i, v, bars);
        load_unit<true>(p, unit_row(min(i + 1, kSteps - 1), grp, mt), t, v);
        if (i & 1) {
          if (warp == 9) {
            asm volatile("bar.sync %0, 96;" ::"r"(7 + (i & 2)) : "memory");
            publish(p, i, grp, 3);
          } else {
            asm volatile("bar.arrive %0, 96;" ::"r"(7 + (i & 2)) : "memory");
          }
        }
      }
    }
  } else {
    asm volatile("setmaxnreg.inc.sync.aligned.u32 224;");
    const int wg = warp >> 2;
    float S[64], O[96];
    uint32_t P[32];
    float m0 = 0.f, m1 = 0.f, l0 = 0.f, l1 = 0.f, h0 = 0.f, h1 = 0.f;
    bool shifted = false;
    auto release = [&](uint32_t bar) {
      if (lane < 2) mbar_arrive_cluster(bar, lane);
    };
    auto stage_o = [&](uint32_t stage, float f0, float f1, int c_lo, int c_hi) {
      const uint32_t addr = stage + ((warp & 3) * 16 + (lane & 15)) * 128 + (((lane >> 4) ^ (lane & 7)) << 4);
#pragma unroll
      for (int j = 4 * c_lo; j < 4 * c_hi; j++) {
        float* o = O + 8 * j;
#pragma unroll
        for (int i = 0; i < 8; i++) o[i] = (i & 2) ? fmaf(o[i], f1, h1) : fmaf(o[i], f0, h0);
        asm volatile("stmatrix.sync.aligned.m8n8.x4.shared.b16 [%0], {%1, %2, %3, %4};" ::"r"(
                         (addr ^ ((j & 3) * 32)) + (j >> 2) * 8192),
                     "r"(pack_bf16(o[0], o[1])), "r"(pack_bf16(o[2], o[3])), "r"(pack_bf16(o[4], o[5])),
                     "r"(pack_bf16(o[6], o[7]))
                     : "memory");
      }
    };
    auto staged = [&]() {
      __syncwarp();
      if (lane == 0) mbar_arrive_local(bars + kBarStaged + 8 * wg);
    };
    float sc0 = 1.f, sc1 = 1.f;
    auto quad_sum = [&](float x) {
      x += __shfl_xor_sync(0xffffffffu, x, 1);
      return x + __shfl_xor_sync(0xffffffffu, x, 2);
    };
    auto finish_l = [&](int wave, float& i0, float& i1) {
      const uint4 vp = lds128(bars + kParV + wave * 32);
      const float a = quad_sum(l0), b = quad_sum(l1);
      i0 = __uint_as_float(vp.z) * rcp(a);
      i1 = __uint_as_float(vp.z) * rcp(b);
      h0 = (a - 2.f * quad_sum(h0)) * i0 * __uint_as_float(vp.y);
      h1 = (b - 2.f * quad_sum(h1)) * i1 * __uint_as_float(vp.y);
    };
    auto issue_qk = [&](int s, int slot0) {
      const uint32_t kb = desc_lo(sbase + kSmemK, 16);
      const uint32_t qb = desc_lo(sbase + kSmemQ, 16) + wg * 1536;
#pragma unroll
      for (int c = 0; c < 3; c++) {
        const int slot = slot0 + c >= 5 ? slot0 + c - 5 : slot0 + c;
        if (c == 2) {
          mbar_wait(bars + kBarFullK2, s & 1);
          if ((s & 15) == 0) mbar_wait(bars + kBarFullQ2 + 8 * wg, (s >> 4) & 1);
        }
#pragma unroll
        for (int kk = 0; kk < 4; kk++)
          wgmma_ss_n128(S, desc64<1024>(qb + c * 512 + kk * 2), desc64<1024>(kb + slot * 1024 + kk * 2),
                        c + kk > 0);
        if (c != 1) wg_commit();
      }
    };
    auto issue_pv = [&](int s) {
      const uint32_t vb = desc_lo(sbase + kSmemV, 1024) + (s & 1) * (kTileBytes >> 4);
      const int acc = (s & 15) != 0;
      auto run = [&](int lo, int hi, int acc0) {
#pragma unroll
        for (int kk = lo; kk < hi; kk++)
          wgmma_rs_n192t(O, P[kk * 4], P[kk * 4 + 1], P[kk * 4 + 2], P[kk * 4 + 3], desc64<3072>(vb + kk * 384),
                         kk > 0 ? 1 : acc0);
      };
      if (acc) {
        wg_fence();
        run(0, 8, 1);
        wg_commit();
      } else {
        wg_fence();
        run(0, 4, 0);
        mbar_wait(bars + kBarFullV2, (s >> 4) & 1);
        wg_fence();
        run(4, 8, 1);
        wg_commit();
      }
    };
    auto shift = [&](int lo, float d0, float d1) {
#pragma unroll
      for (int i = lo; i < 64; i += 4) {
        S[i] -= d0;
        S[i + 1] -= d0;
        S[i + 2] -= d1;
        S[i + 3] -= d1;
      }
    };
    auto unsafe = [&](int lo, int hi, bool first) {
      int a0 = 0, a1 = 0, b0 = 0, b1 = 0;
#pragma unroll
      for (int i = lo; i < hi; i += 8) {
        a0 = __vimax3_s32(a0, __float_as_int(S[i]), __float_as_int(S[i + 1]));
        a1 = __vimax3_s32(a1, __float_as_int(S[i + 2]), __float_as_int(S[i + 3]));
        b0 = __vimax3_s32(b0, __float_as_int(S[i + 4]), __float_as_int(S[i + 5]));
        b1 = __vimax3_s32(b1, __float_as_int(S[i + 6]), __float_as_int(S[i + 7]));
      }
      bool bad = __vimax3_s32(max(a0, b0), a1, b1) > __float_as_int(kLazyAbove);
      if (first) {
        uint32_t u0 = ~0u, u1 = ~0u;
#pragma unroll
        for (int i = 0; i < 16; i += 4) {
          u0 = __vimin3_u32(u0, __float_as_uint(S[i]), __float_as_uint(S[i + 1]));
          u1 = __vimin3_u32(u1, __float_as_uint(S[i + 2]), __float_as_uint(S[i + 3]));
        }
        bad |= max(u0, u1) >= __float_as_uint(-kLazyBelow);
      }
      return __any_sync(0xffffffffu, bad);
    };
    auto use_true_max = [&](int lo, bool first, bool boundary, float& f0, float& f1) {
      float d0 = S[lo], d1 = S[lo + 2];
#pragma unroll
      for (int i = lo; i < 64; i += 4) {
        d0 = fmaxf(d0, fmaxf(S[i], S[i + 1]));
        d1 = fmaxf(d1, fmaxf(S[i + 2], S[i + 3]));
      }
      d0 = fmaxf(d0, __shfl_xor_sync(0xffffffffu, d0, 1));
      d1 = fmaxf(d1, __shfl_xor_sync(0xffffffffu, d1, 1));
      d0 = fmaxf(d0, __shfl_xor_sync(0xffffffffu, d0, 2));
      d1 = fmaxf(d1, __shfl_xor_sync(0xffffffffu, d1, 2));
      if (!first) {
        d0 = fmaxf(d0, 0.f);
        d1 = fmaxf(d1, 0.f);
        f0 = ex2(-d0);
        f1 = ex2(-d1);
        l0 *= f0;
        l1 *= f1;
        if (!boundary) {
          h0 *= f0;
          h1 *= f1;
        }
#pragma unroll
        for (int i = 0; i < lo; i++) S[i] *= (i & 2) ? f1 : f0;
      }
      shift(lo, d0, d1);
      m0 += d0;
      m1 += d1;
      shifted = true;
    };
    auto exps = [&](int lo, int hi) {
#pragma unroll
      for (int i = lo; i < hi; i += 4) {
        S[i] = ex2(S[i]);
        S[i + 1] = ex2(S[i + 1]);
        S[i + 2] = ex2(S[i + 2]);
        S[i + 3] = ex2(S[i + 3]);
        l0 += S[i] + S[i + 1];
        l1 += S[i + 2] + S[i + 3];
      }
    };
    auto to_p = [&]() {
#pragma unroll
      for (int j = 0; j < 32; j++) P[j] = pack_f16(S[2 * j], S[2 * j + 1]);
    };
    auto scale_o = [&](float f0, float f1) {
#pragma unroll
      for (int i = 0; i < 96; i += 4) {
        O[i] *= f0;
        O[i + 1] *= f0;
        O[i + 2] *= f1;
        O[i + 3] *= f1;
      }
    };
#pragma unroll
    for (int i = 0; i < 96; i++) asm volatile("" : "=f"(O[i]));
#pragma unroll
    for (int i = 0; i < 32; i++) asm volatile("" : "=r"(P[i]));
    if (threadIdx.x == 128) asm volatile("prefetch.tensormap [%0];" ::"l"(&tmo) : "memory");
    if (wg == 1) bar_arrive(1);
    int slot0 = 2;
#pragma unroll 1
    for (int s = 0;; s++) {
      const bool boundary = (s & 15) == 0;
      slot0 = slot0 >= 2 ? slot0 - 2 : slot0 + 3;
      if (boundary) mbar_wait(bars + kBarFullQ + 8 * wg, (s >> 4) & 1);
      mbar_wait(bars + kBarFullK01 + 8 * (s & 1), (s >> 1) & 1);
      bar_sync(1 + wg);
      pin(P);
      pin(O);
      wg_fence();
      issue_qk(s, slot0);
      mbar_wait(bars + kBarFullV + 8 * ((s - 1) & 1), ((s - 1) >> 1) & 1);
      wg_wait<1>();
      release(bars + kBarEmptyK0);
      if (s > 0) issue_pv(s - 1);
      else wg_commit();
      bar_arrive(2 - wg);
      wg_wait<1>();
      pin(S);
      release(bars + kBarEmptyK12 + 8 * (s & 1));
      if ((s & 15) == 15 && lane == 0) mbar_arrive_local(bars + kBarEmptyQ + 8 * wg);
      if (shifted) shift(0, m0, m1);
      bool rescale = unsafe(0, kExpSplit, boundary);
      if (rescale) use_true_max(0, boundary, boundary, sc0, sc1);
      const bool late = unsafe(kExpSplit, 64, false);
      exps(0, kExpSplit);
      pin(S);
      asm volatile("st.volatile.shared.f32 [%0], %1;" ::"r"(bars + kDummy), "f"(l0 + l1) : "memory");
      wg_wait<0>();
      pin(O);
      pin(P);
      if (s > 0) {
        release(bars + kBarEmptyV + 8 * ((s - 1) & 1));
        if (((s + wg) & 15) == 0 && lane == 0) mbar_arrive_local(bars + kBarStage + 8 * (1 - wg));
      }
      if (late) {
        float f0, f1;
        use_true_max(kExpSplit, false, boundary, f0, f1);
        if (!boundary) {
          sc0 = f0;
          sc1 = f1;
          rescale = true;
        }
      }
      if (boundary && s > 0) {
        mbar_wait(bars + kBarStage + 8 * wg, ((s >> 4) - 1) & 1);
        stage_o(sbase + kSmemV + wg * kTileBytes + kTileBytes / 2, sc0, sc1, 0, 3);
        staged();
      } else if (rescale && s > 0) {
        scale_o(sc0, sc1);
      }
      pin(S);
      exps(kExpSplit, 64);
      to_p();
      if ((s & 15) == 7) {
        h0 = l0;
        h1 = l1;
      }
      if ((s & 15) == 15) {
        finish_l(s >> 4, sc0, sc1);
        m0 = m1 = l0 = l1 = 0.f;
        shifted = false;
      }
      if (s == own - 1) break;
    }
    uint32_t vw = pick(tail, kPlacesV<1>, kPlacesV<2>, kPlacesV<3>);
    uint32_t pw = wg ? pick(tail, kPlacesP<1, 1>, kPlacesP<2, 1>, kPlacesP<3, 1>)
                     : pick(tail, kPlacesP<1, 0>, kPlacesP<2, 0>, kPlacesP<3, 0>);
    auto next_v = [&]() {
      mbar_spin(bars + (vw >> 1 & 0x78), vw >> 2 & 1);
      const uint32_t vb = desc_lo(sbase, 1024) + (vw & 11) * 1024;
      vw >>= 8;
      return vb;
    };
    bool rescale = false;
    const float4* extra = (const float4*)(p.prob + (size_t)(blockIdx.x * kProbBytes + kProbExtra + (threadIdx.x >> 2) * 16));
    auto next_p = [&]() {
      mbar_spin(bars + (pw >> 1 & 0xF8), pw >> 3 & 1);
      const uint32_t a = sbase + (pw & 7) * 16384 + (threadIdx.x & 127) * 16;
      pw >>= 10;
      if (rescale) {
        const float4 b = __ldcg(extra);
        extra += 64;
        scale_p(a, ex2(b.x - m0), ex2(b.y - m1));
      }
      return a;
    };
    auto take = [&](uint32_t (&A)[32], uint32_t a) {
#pragma unroll
      for (int i = 0; i < 8; i++) {
        const uint4 x = lds128v(a + i * 2048);
        A[4 * i] = x.x, A[4 * i + 1] = x.y, A[4 * i + 2] = x.z, A[4 * i + 3] = x.w;
      }
      pin(A);
    };
    float f0 = 1.f, f1 = 1.f;
    uint32_t pa;
#pragma unroll 1
    for (int x = 0;; x++) {
      const uint32_t vb = next_v();
      bar_sync(1 + wg);
      pin(P);
      pin(O);
      wg_fence();
#pragma unroll
      for (int kk = 0; kk < 8; kk++)
        wgmma_rs_n192t(O, P[kk * 4], P[kk * 4 + 1], P[kk * 4 + 2], P[kk * 4 + 3], desc64<3072>(vb + kk * 384), 1);
      wg_commit();
      if (x < tail - 1) bar_arrive(2 - wg);
      if (x == 0) {
        mbar_spin(bars + kBarUnits, 1);
        const uint2 r = lds64(bars + kOffK + (threadIdx.x >> 2) * 8);
        float r0 = __uint_as_float(r.x), r1 = __uint_as_float(r.y);
        rescale = shifted || __any_sync(0xffffffffu, r0 < 0.f);
        if (rescale) {
          float n0 = m0, n1 = m1;
          r0 = r1 = 0.f;
#pragma unroll 1
          for (int j = 0;; j++) {
            const float4 b = __ldcg(extra + j * 64);
            const float x0 = fmaxf(n0, b.x), x1 = fmaxf(n1, b.y);
            r0 = r0 * ex2(n0 - x0) + b.z * ex2(b.x - x0);
            r1 = r1 * ex2(n1 - x1) + b.w * ex2(b.y - x1);
            n0 = x0;
            n1 = x1;
            if (j == tail - 1) break;
          }
          f0 = ex2(m0 - n0);
          f1 = ex2(m1 - n1);
          l0 *= f0;
          l1 *= f1;
          h0 *= f0;
          h1 *= f1;
          m0 = n0;
          m1 = n1;
        }
        l0 += r0;
        l1 += r1;
        finish_l(kWaves - 1, sc0, sc1);
        asm volatile("st.volatile.shared.f32 [%0], %1;" ::"r"(bars + kDummy), "f"(h0 + h1) : "memory");
      }
      pa = next_p();
      if (x == tail - 1) break;
      wg_wait<0>();
      pin(O);
      pin(P);
      if (rescale && x == 0) {
        scale_o(f0, f1);
        f0 = f1 = 1.f;
      }
      take(P, pa);
      release(bars + kBarEmptyV + 8 * ((own - 1 + x) & 1));
    }
    cluster_arrive();
    uint32_t R[32];
    take(R, pa);
    const uint32_t v_last = next_v();
    float T0[32], T1[32];
    auto tail_pv = [&](float (&T)[32], int c) {
      const uint32_t vb = v_last + c * 64;
      wg_fence();
#pragma unroll
      for (int kk = 0; kk < 8; kk++)
        wgmma_rs_n64t(T, R[kk * 4], R[kk * 4 + 1], R[kk * 4 + 2], R[kk * 4 + 3], desc64<3072>(vb + kk * 384), kk > 0);
      wg_commit();
    };
    uint32_t X[16];
    auto tail_pack = [&](float (&T)[32], int c) {
      pin(T);
#pragma unroll
      for (int i = 0; i < 16; i++) {
        const float f = (i & 1) ? sc1 : sc0;
        X[i] = pack_bf16(fmaf(T[2 * i], f, O[32 * c + 2 * i]), fmaf(T[2 * i + 1], f, O[32 * c + 2 * i + 1]));
      }
      pin(X);
    };
    auto tail_store = [&](int c) {
      const uint32_t addr = sbase + tail_stage + wg * (kTileBytes / 2) + c * 8192 +
                            ((warp & 3) * 16 + (lane & 15)) * 128 + (((lane >> 4) ^ (lane & 7)) << 4);
#pragma unroll
      for (int j = 0; j < 4; j++)
        asm volatile("stmatrix.sync.aligned.m8n8.x4.shared.b16 [%0], {%1, %2, %3, %4};" ::"r"(addr ^ (j * 32)), "r"(X[4 * j]),
                     "r"(X[4 * j + 1]), "r"(X[4 * j + 2]), "r"(X[4 * j + 3])
                     : "memory");
      __syncwarp();
      if (lane == 0) mbar_arrive_local(bars + kBarTail + 24 * wg + 8 * c);
    };
    tail_pv(T0, 0);
    f0 *= sc0;
    f1 *= sc1;
    wg_wait<1>();
    pin(P);
    auto prescale = [&](int c) {
      pin(O);
#pragma unroll
      for (int i = 32 * c; i < 32 * c + 32; i++) O[i] = (i & 2) ? fmaf(O[i], f1, h1) : fmaf(O[i], f0, h0);
      pin(O);
      mbar_spin(bars + kBarEmptyV + 8, 0);
    };
    prescale(0);
    tail_pv(T1, 1);
    if (wg == 0) bar_arrive(2);
    wg_wait<1>();
    tail_pack(T0, 0);
    tail_store(0);
    tail_pv(T0, 2);
    prescale(1);
    wg_wait<1>();
    tail_pack(T1, 1);
    tail_store(1);
    prescale(2);
    wg_wait<0>();
    tail_pack(T0, 2);
    tail_store(2);
    cluster_wait();
  }
}

}

extern "C" void kernel_launch(void* const* d_in, const int* in_sizes, int n_in, void* d_out, int out_size) {
  static CUtensorMap tmq, tmo;
  static const void *tm_q = nullptr, *tm_o = nullptr;
  static void *scratch, *flags, *prob;
  if (tm_q != d_in[0] || tm_o != d_out) {
    typedef CUresult (*EncodeFn)(CUtensorMap*, CUtensorMapDataType, cuuint32_t, void*, const cuuint64_t*,
                                 const cuuint64_t*, const cuuint32_t*, const cuuint32_t*, CUtensorMapInterleave,
                                 CUtensorMapSwizzle, CUtensorMapL2promotion, CUtensorMapFloatOOBfill);
    void* fn = nullptr;
    cudaDriverEntryPointQueryResult qr;
    cudaGetDriverEntryPoint("cuTensorMapEncodeTiled", &fn, cudaEnableDefault, &qr);
    cuuint64_t dims[2] = {(cuuint64_t)kD, (cuuint64_t)kH * kS};
    cuuint64_t strides[1] = {(cuuint64_t)kD * 2};
    cuuint32_t box[2] = {64, 64};
    cuuint32_t estr[2] = {1, 1};
    ((EncodeFn)fn)(&tmq, CU_TENSOR_MAP_DATA_TYPE_BFLOAT16, 2, d_in[0], dims, strides, box, estr,
                   CU_TENSOR_MAP_INTERLEAVE_NONE, CU_TENSOR_MAP_SWIZZLE_128B, CU_TENSOR_MAP_L2_PROMOTION_L2_128B,
                   CU_TENSOR_MAP_FLOAT_OOB_FILL_NONE);
    ((EncodeFn)fn)(&tmo, CU_TENSOR_MAP_DATA_TYPE_BFLOAT16, 2, d_out, dims, strides, box, estr,
                   CU_TENSOR_MAP_INTERLEAVE_NONE, CU_TENSOR_MAP_SWIZZLE_128B, CU_TENSOR_MAP_L2_PROMOTION_NONE,
                   CU_TENSOR_MAP_FLOAT_OOB_FILL_NONE);
    cudaFuncSetAttribute(attn_kernel, cudaFuncAttributeMaxDynamicSharedMemorySize, kSmemTotal);
    cudaGetSymbolAddress(&scratch, g_scratch);
    cudaGetSymbolAddress(&flags, g_flags);
    cudaGetSymbolAddress(&prob, g_prob);
    tm_q = d_in[0];
    tm_o = d_out;
  }
  Params p;
  p.q = (const __nv_bfloat16*)d_in[0];
  p.qk = (const int*)d_in[1];
  p.qv = (const int*)d_in[2];
  p.ks = (const __nv_bfloat16*)d_in[3];
  p.kz = (const __nv_bfloat16*)d_in[4];
  p.vs = (const __nv_bfloat16*)d_in[5];
  p.vz = (const __nv_bfloat16*)d_in[6];
  p.scratch = (uint8_t*)scratch;
  p.flags = (unsigned*)flags;
  p.prob = (uint8_t*)prob;
  attn_kernel<<<kOwners + kHelpers, 384, kSmemTotal>>>(p, tmq, tmo);
}
```
